```python
import torch

def _softmax(x, axis=-1):
    return torch.softmax(x, dim=axis)
def _gelu(x):
    return torch.nn.functional.gelu(x, approximate="tanh")
def _silu(x):
    return torch.nn.functional.silu(x)
def _sigmoid(x):
    return torch.sigmoid(x)
def _layernorm(x, axis=-1, eps=1e-5):
    m = x.mean(dim=axis, keepdim=True)
    v = x.var(dim=axis, keepdim=True, unbiased=False)
    return (x - m) / torch.sqrt(v + eps)
def _scatter_add(tgt, idx, src, axis=0):
    return tgt.clone().index_add_(axis, idx, src)
def _segment_sum(src, seg, n):
    out = torch.zeros((n,) + src.shape[1:], dtype=src.dtype)
    return out.index_add_(0, seg, src)
def _pad(x, pw):
    flat = tuple(v for pair in reversed(pw) for v in pair)
    return torch.nn.functional.pad(x, flat)

kernel_name = 'sequential_preLN__ssm_conv_s4__glu_gated_glu__prompt'

def setup_inputs():

    _w = (lambda a: (lambda t: t.to(torch.bfloat16) if t.is_floating_point() else t)(torch.as_tensor(a)))
    def _A_setup():
        B, L, D, N = 1, 2048, 448, 256
        A_re = -(lambda _x: torch.exp(torch.as_tensor(_x)))((lambda *s: torch.randn(*s, dtype=torch.bfloat16) * 3.2)(D, N))
        A_im = torch.pi * (lambda *s: torch.randn(*s, dtype=torch.bfloat16) * 0.05)(D, N)
        B_re = (lambda *s: torch.randn(*s, dtype=torch.bfloat16) * 0.05)(D, N)
        B_im = (lambda *s: torch.randn(*s, dtype=torch.bfloat16) * 0.05)(D, N)
        C_re = (lambda *s: torch.randn(*s, dtype=torch.bfloat16) * 0.05)(D, N)
        C_im = (lambda *s: torch.randn(*s, dtype=torch.bfloat16) * 0.05)(D, N)
        log_dt = (lambda *s: torch.randn(*s, dtype=torch.bfloat16) * 0.05)(D) * 0.5 - 4.0
        Dskip = (lambda *s: torch.randn(*s, dtype=torch.bfloat16) * 0.05)(D)
        return {
            "u": _w((lambda *s: torch.randn(*s, dtype=torch.bfloat16) * 0.05)(B, L, D)),
            "A_re": _w(A_re),
            "A_im": _w(A_im),
            "B_re": _w(B_re),
            "B_im": _w(B_im),
            "C_re": _w(C_re),
            "C_im": _w(C_im),
            "log_dt": _w(log_dt),
            "Dskip": _w(Dskip),
        }
    _A_in = _A_setup()

    def _B_setup():
        B, S, D, F = 1, 2048, 448, 1792
        return {
            "x": _w((lambda *s: torch.randn(*s, dtype=torch.bfloat16) * 0.05)(B, S, D)),
            "w_gate": _w((lambda *s: torch.randn(*s, dtype=torch.bfloat16) * 0.05)(D, F)),
            "w_up": _w((lambda *s: torch.randn(*s, dtype=torch.bfloat16) * 0.05)(D, F)),
            "w_down": _w((lambda *s: torch.randn(*s, dtype=torch.bfloat16) * 0.05)(F, D)),
        }
    _B_in = _B_setup()

    return {
        "A_u": _A_in["u"],
        "A_A_re": _A_in["A_re"],
        "A_A_im": _A_in["A_im"],
        "A_B_re": _A_in["B_re"],
        "A_B_im": _A_in["B_im"],
        "A_C_re": _A_in["C_re"],
        "A_C_im": _A_in["C_im"],
        "A_log_dt": _A_in["log_dt"],
        "A_Dskip": _A_in["Dskip"],
        "B_x": _B_in["x"],
        "B_w_gate": _B_in["w_gate"],
        "B_w_up": _B_in["w_up"],
        "B_w_down": _B_in["w_down"],
    }

def reference(A_u, A_A_re, A_A_im, A_B_re, A_B_im, A_C_re, A_C_im, A_log_dt, A_Dskip, B_x, B_w_gate, B_w_up, B_w_down):
    def _A_ref(u, A_re, A_im, B_re, B_im, C_re, C_im, log_dt, Dskip):
        Bsz, L, D = u.shape
        dt = torch.exp(log_dt)[:, None]
        A = A_re + 1j * A_im
        Bc = B_re + 1j * B_im
        Cc = C_re + 1j * C_im
        logdA = dt * A
        dB = dt * Bc
        l = (lambda x, dt: x.to(dt))(torch.arange(L), A_re.dtype)
        P = torch.exp(logdA[:, :, None] * l[None, None, :])
        K = torch.einsum("dn,dnl,dn->dl", Cc, P, dB).real
        L2 = 2 * L
        Kp = _pad(K, ((0, 0), (0, L)))
        up = (lambda x, *d: x.permute(*d))(u, 0, 2, 1)
        up = _pad(up, ((0, 0), (0, 0), (0, L)))
        Kf = (lambda x, axes=(-2,-1): torch.fft.rfft2(x.float(), dim=axes))(Kp[:, None, :], axes=(-2, -1))
        Uf = (lambda x, axes=(-2,-1): torch.fft.rfft2(x.float(), dim=axes))(up[:, :, None, :], axes=(-2, -1))
        Yf = Uf * Kf[None, :, :, :]
        y = (lambda x, s, axes=(-2,-1): torch.fft.irfft2(x, s=s, dim=axes).to(torch.bfloat16))(Yf, (1, L2), axes=(-2, -1))[:, :, 0, :L]
        y = (lambda x, *d: x.permute(*d))(y, 0, 2, 1) + u * Dskip[None, None, :]
        return y

    def _B_ref(x, w_gate, w_up, w_down):
        g = torch.einsum("bsd,df->bsf", x, w_gate)
        u = torch.einsum("bsd,df->bsf", x, w_up)
        h = _sigmoid(g) * u
        return torch.einsum("bsf,fd->bsd", h, w_down)

    x = A_u
    h = x + _A_ref(_layernorm(x, axis=-1), A_A_re, A_A_im, A_B_re, A_B_im, A_C_re, A_C_im, A_log_dt, A_Dskip)
    h2 = h + _B_ref(_layernorm(h, axis=-1), B_w_gate, B_w_up, B_w_down)
    return h2
```

```cpp
#include <cuda_runtime.h>
#include <cuda_bf16.h>
#include <cuda.h>
#include <stdint.h>

constexpr int L_ = 2048, D_ = 448, NM_ = 256, F_ = 1792;

__device__ __align__(1024) __nv_bfloat16 g_hT[D_ * L_];
__device__ __align__(16) uint32_t g_stats[L_];
__device__ __align__(16) float g_csum[2 * F_];
__device__ __align__(16) uint4 g_H[16 * 8 * 8 * 14 * 32];
__device__ __align__(16) uint32_t g_flags[16 * 8 * 8 * 2];

__device__ __forceinline__ uint32_t smem_u32(const void* p) { return (uint32_t)__cvta_generic_to_shared(p); }
__device__ __forceinline__ void mbar_init(uint32_t bar, int cnt) { asm volatile("mbarrier.init.shared::cta.b64 [%0], %1;" ::"r"(bar), "r"(cnt)); }
__device__ __forceinline__ void mbar_expect_tx(uint32_t bar, uint32_t bytes) {
  asm volatile("mbarrier.arrive.expect_tx.shared::cta.b64 _, [%0], %1;" ::"r"(bar), "r"(bytes) : "memory");
}
__device__ __forceinline__ void mbar_arrive(uint32_t bar) { asm volatile("mbarrier.arrive.shared::cta.b64 _, [%0];" ::"r"(bar) : "memory"); }
__device__ __forceinline__ void mbar_arrive_remote(uint32_t bar_cluster) {
  asm volatile("mbarrier.arrive.release.cluster.shared::cluster.b64 _, [%0];" ::"r"(bar_cluster) : "memory");
}
__device__ __forceinline__ void mbar_wait(uint32_t bar, uint32_t parity) {
  uint32_t ok;
  int it = 0;
  do {
    asm volatile("{\n.reg .pred p;\nmbarrier.try_wait.parity.shared::cta.b64 p, [%1], %2;\nselp.u32 %0, 1, 0, p;\n}"
                 : "=r"(ok) : "r"(bar), "r"(parity) : "memory");
    if (++it > (1 << 22)) __trap();
  } while (!ok);
}
__device__ __forceinline__ void mbar_wait_cluster(uint32_t bar, uint32_t parity) {
  uint32_t ok;
  int it = 0;
  do {
    asm volatile("{\n.reg .pred p;\nmbarrier.try_wait.parity.acquire.cluster.shared::cta.b64 p, [%1], %2;\nselp.u32 %0, 1, 0, p;\n}"
                 : "=r"(ok) : "r"(bar), "r"(parity) : "memory");
    if (++it > (1 << 22)) __trap();
  } while (!ok);
}
__device__ __forceinline__ void bar_sync(int id, int n) { asm volatile("bar.sync %0, %1;" ::"r"(id), "r"(n) : "memory"); }
__device__ __forceinline__ void bar_arrive(int id, int n) { asm volatile("bar.arrive %0, %1;" ::"r"(id), "r"(n) : "memory"); }
__device__ __forceinline__ void fence_proxy_async() { asm volatile("fence.proxy.async.shared::cta;" ::: "memory"); }
#define WG_FENCE() asm volatile("wgmma.fence.sync.aligned;" ::: "memory")
#define WG_COMMIT() asm volatile("wgmma.commit_group.sync.aligned;" ::: "memory")
#define WG_WAIT(n) asm volatile("wgmma.wait_group.sync.aligned %0;" ::"n"(n) : "memory")
__device__ __forceinline__ uint64_t mkdesc(uint32_t addr, uint32_t lbo, uint32_t sbo, int swz) {
  return (uint64_t)((addr & 0x3FFFF) >> 4) | ((uint64_t)(lbo >> 4) << 16) | ((uint64_t)(sbo >> 4) << 32) | ((uint64_t)swz << 62);
}
__device__ __forceinline__ uint32_t pack_bf16(float lo, float hi) {
  uint32_t r;
  asm("cvt.rn.bf16x2.f32 %0, %1, %2;" : "=r"(r) : "f"(hi), "f"(lo));
  return r;
}
__device__ __forceinline__ float bf_lo(uint32_t v) { return __uint_as_float(v << 16); }
__device__ __forceinline__ float bf_hi(uint32_t v) { return __uint_as_float(v & 0xFFFF0000u); }
__device__ __forceinline__ float bf_round(float x) { return __bfloat162float(__float2bfloat16_rn(x)); }
__device__ __forceinline__ void tma_load_2d(uint32_t dst, const CUtensorMap* tm, int x, int y, uint32_t bar) {
  asm volatile("cp.async.bulk.tensor.2d.shared::cluster.global.mbarrier::complete_tx::bytes [%0], [%1, {%3, %4}], [%2];"
               ::"r"(dst), "l"((uint64_t)tm), "r"(bar), "r"(x), "r"(y) : "memory");
}
__device__ __forceinline__ void ldsm_x4_t(uint32_t& r0, uint32_t& r1, uint32_t& r2, uint32_t& r3, uint32_t addr) {
  asm volatile("ldmatrix.sync.aligned.m8n8.x4.trans.shared.b16 {%0,%1,%2,%3}, [%4];" : "=r"(r0), "=r"(r1), "=r"(r2), "=r"(r3) : "r"(addr) : "memory");
}
__device__ __forceinline__ void ldsm_x2_t(uint32_t& r0, uint32_t& r1, uint32_t addr) {
  asm volatile("ldmatrix.sync.aligned.m8n8.x2.trans.shared.b16 {%0,%1}, [%2];" : "=r"(r0), "=r"(r1) : "r"(addr) : "memory");
}
__device__ __forceinline__ void mma16816(float (&c)[4], uint32_t a0, uint32_t a1, uint32_t a2, uint32_t a3, uint32_t b0, uint32_t b1) {
  asm volatile("mma.sync.aligned.m16n8k16.row.col.f32.bf16.bf16.f32 {%0,%1,%2,%3}, {%4,%5,%6,%7}, {%8,%9}, {%0,%1,%2,%3};"
               : "+f"(c[0]), "+f"(c[1]), "+f"(c[2]), "+f"(c[3]) : "r"(a0), "r"(a1), "r"(a2), "r"(a3), "r"(b0), "r"(b1));
}
__device__ __forceinline__ void sts128(uint32_t addr, uint32_t a, uint32_t b, uint32_t c, uint32_t d) {
  asm volatile("st.shared.v4.b32 [%0], {%1,%2,%3,%4};" ::"r"(addr), "r"(a), "r"(b), "r"(c), "r"(d) : "memory");
}
__device__ __forceinline__ uint32_t lds32(uint32_t addr) {
  uint32_t r;
  asm volatile("ld.shared.b32 %0, [%1];" : "=r"(r) : "r"(addr) : "memory");
  return r;
}
__device__ __forceinline__ uint4 lds128(uint32_t addr) {
  uint4 r;
  asm volatile("ld.shared.v4.b32 {%0,%1,%2,%3}, [%4];" : "=r"(r.x), "=r"(r.y), "=r"(r.z), "=r"(r.w) : "r"(addr) : "memory");
  return r;
}
__device__ __forceinline__ uint2 lds64(uint32_t addr) {
  uint2 r;
  asm volatile("ld.shared.v2.b32 {%0,%1}, [%2];" : "=r"(r.x), "=r"(r.y) : "r"(addr) : "memory");
  return r;
}

template<int TA, int TB> __device__ __forceinline__ void wgmma_ss_n256(float (&d)[128], uint64_t da, uint64_t db, int scale_d) {
  asm volatile("{\n.reg .pred p;\nsetp.ne.b32 p, %130, 0;\n"
    "wgmma.mma_async.sync.aligned.m64n256k16.f32.bf16.bf16 {%0, %1, %2, %3, %4, %5, %6, %7, %8, %9, %10, %11, %12, %13, %14, %15, %16, %17, %18, %19, %20, %21, %22, %23, %24, %25, %26, %27, %28, %29, %30, %31, %32, %33, %34, %35, %36, %37, %38, %39, %40, %41, %42, %43, %44, %45, %46, %47, %48, %49, %50, %51, %52, %53, %54, %55, %56, %57, %58, %59, %60, %61, %62, %63, %64, %65, %66, %67, %68, %69, %70, %71, %72, %73, %74, %75, %76, %77, %78, %79, %80, %81, %82, %83, %84, %85, %86, %87, %88, %89, %90, %91, %92, %93, %94, %95, %96, %97, %98, %99, %100, %101, %102, %103, %104, %105, %106, %107, %108, %109, %110, %111, %112, %113, %114, %115, %116, %117, %118, %119, %120, %121, %122, %123, %124, %125, %126, %127}, %128, %129, p, 1, 1, %131, %132;\n}"
    : "+f"(d[0]), "+f"(d[1]), "+f"(d[2]), "+f"(d[3]), "+f"(d[4]), "+f"(d[5]), "+f"(d[6]), "+f"(d[7]), "+f"(d[8]), "+f"(d[9]), "+f"(d[10]), "+f"(d[11]), "+f"(d[12]), "+f"(d[13]), "+f"(d[14]), "+f"(d[15]), "+f"(d[16]), "+f"(d[17]), "+f"(d[18]), "+f"(d[19]), "+f"(d[20]), "+f"(d[21]), "+f"(d[22]), "+f"(d[23]), "+f"(d[24]), "+f"(d[25]), "+f"(d[26]), "+f"(d[27]), "+f"(d[28]), "+f"(d[29]), "+f"(d[30]), "+f"(d[31]), "+f"(d[32]), "+f"(d[33]), "+f"(d[34]), "+f"(d[35]), "+f"(d[36]), "+f"(d[37]), "+f"(d[38]), "+f"(d[39]), "+f"(d[40]), "+f"(d[41]), "+f"(d[42]), "+f"(d[43]), "+f"(d[44]), "+f"(d[45]), "+f"(d[46]), "+f"(d[47]), "+f"(d[48]), "+f"(d[49]), "+f"(d[50]), "+f"(d[51]), "+f"(d[52]), "+f"(d[53]), "+f"(d[54]), "+f"(d[55]), "+f"(d[56]), "+f"(d[57]), "+f"(d[58]), "+f"(d[59]), "+f"(d[60]), "+f"(d[61]), "+f"(d[62]), "+f"(d[63]), "+f"(d[64]), "+f"(d[65]), "+f"(d[66]), "+f"(d[67]), "+f"(d[68]), "+f"(d[69]), "+f"(d[70]), "+f"(d[71]), "+f"(d[72]), "+f"(d[73]), "+f"(d[74]), "+f"(d[75]), "+f"(d[76]), "+f"(d[77]), "+f"(d[78]), "+f"(d[79]), "+f"(d[80]), "+f"(d[81]), "+f"(d[82]), "+f"(d[83]), "+f"(d[84]), "+f"(d[85]), "+f"(d[86]), "+f"(d[87]), "+f"(d[88]), "+f"(d[89]), "+f"(d[90]), "+f"(d[91]), "+f"(d[92]), "+f"(d[93]), "+f"(d[94]), "+f"(d[95]), "+f"(d[96]), "+f"(d[97]), "+f"(d[98]), "+f"(d[99]), "+f"(d[100]), "+f"(d[101]), "+f"(d[102]), "+f"(d[103]), "+f"(d[104]), "+f"(d[105]), "+f"(d[106]), "+f"(d[107]), "+f"(d[108]), "+f"(d[109]), "+f"(d[110]), "+f"(d[111]), "+f"(d[112]), "+f"(d[113]), "+f"(d[114]), "+f"(d[115]), "+f"(d[116]), "+f"(d[117]), "+f"(d[118]), "+f"(d[119]), "+f"(d[120]), "+f"(d[121]), "+f"(d[122]), "+f"(d[123]), "+f"(d[124]), "+f"(d[125]), "+f"(d[126]), "+f"(d[127])
    : "l"(da), "l"(db), "r"(scale_d), "n"(TA), "n"(TB));
}
template<int TA, int TB> __device__ __forceinline__ void wgmma_ss_n128(float (&d)[64], uint64_t da, uint64_t db, int scale_d) {
  asm volatile("{\n.reg .pred p;\nsetp.ne.b32 p, %66, 0;\n"
    "wgmma.mma_async.sync.aligned.m64n128k16.f32.bf16.bf16 {%0, %1, %2, %3, %4, %5, %6, %7, %8, %9, %10, %11, %12, %13, %14, %15, %16, %17, %18, %19, %20, %21, %22, %23, %24, %25, %26, %27, %28, %29, %30, %31, %32, %33, %34, %35, %36, %37, %38, %39, %40, %41, %42, %43, %44, %45, %46, %47, %48, %49, %50, %51, %52, %53, %54, %55, %56, %57, %58, %59, %60, %61, %62, %63}, %64, %65, p, 1, 1, %67, %68;\n}"
    : "+f"(d[0]), "+f"(d[1]), "+f"(d[2]), "+f"(d[3]), "+f"(d[4]), "+f"(d[5]), "+f"(d[6]), "+f"(d[7]), "+f"(d[8]), "+f"(d[9]), "+f"(d[10]), "+f"(d[11]), "+f"(d[12]), "+f"(d[13]), "+f"(d[14]), "+f"(d[15]), "+f"(d[16]), "+f"(d[17]), "+f"(d[18]), "+f"(d[19]), "+f"(d[20]), "+f"(d[21]), "+f"(d[22]), "+f"(d[23]), "+f"(d[24]), "+f"(d[25]), "+f"(d[26]), "+f"(d[27]), "+f"(d[28]), "+f"(d[29]), "+f"(d[30]), "+f"(d[31]), "+f"(d[32]), "+f"(d[33]), "+f"(d[34]), "+f"(d[35]), "+f"(d[36]), "+f"(d[37]), "+f"(d[38]), "+f"(d[39]), "+f"(d[40]), "+f"(d[41]), "+f"(d[42]), "+f"(d[43]), "+f"(d[44]), "+f"(d[45]), "+f"(d[46]), "+f"(d[47]), "+f"(d[48]), "+f"(d[49]), "+f"(d[50]), "+f"(d[51]), "+f"(d[52]), "+f"(d[53]), "+f"(d[54]), "+f"(d[55]), "+f"(d[56]), "+f"(d[57]), "+f"(d[58]), "+f"(d[59]), "+f"(d[60]), "+f"(d[61]), "+f"(d[62]), "+f"(d[63])
    : "l"(da), "l"(db), "r"(scale_d), "n"(TA), "n"(TB));
}
template<int TA, int TB> __device__ __forceinline__ void wgmma_ss_n64(float (&d)[32], uint64_t da, uint64_t db, int scale_d) {
  asm volatile("{\n.reg .pred p;\nsetp.ne.b32 p, %34, 0;\n"
    "wgmma.mma_async.sync.aligned.m64n64k16.f32.bf16.bf16 {%0, %1, %2, %3, %4, %5, %6, %7, %8, %9, %10, %11, %12, %13, %14, %15, %16, %17, %18, %19, %20, %21, %22, %23, %24, %25, %26, %27, %28, %29, %30, %31}, %32, %33, p, 1, 1, %35, %36;\n}"
    : "+f"(d[0]), "+f"(d[1]), "+f"(d[2]), "+f"(d[3]), "+f"(d[4]), "+f"(d[5]), "+f"(d[6]), "+f"(d[7]), "+f"(d[8]), "+f"(d[9]), "+f"(d[10]), "+f"(d[11]), "+f"(d[12]), "+f"(d[13]), "+f"(d[14]), "+f"(d[15]), "+f"(d[16]), "+f"(d[17]), "+f"(d[18]), "+f"(d[19]), "+f"(d[20]), "+f"(d[21]), "+f"(d[22]), "+f"(d[23]), "+f"(d[24]), "+f"(d[25]), "+f"(d[26]), "+f"(d[27]), "+f"(d[28]), "+f"(d[29]), "+f"(d[30]), "+f"(d[31])
    : "l"(da), "l"(db), "r"(scale_d), "n"(TA), "n"(TB));
}
template<int TB> __device__ __forceinline__ void wgmma_rs_n112(float (&d)[56], uint32_t a0, uint32_t a1, uint32_t a2, uint32_t a3, uint64_t db, int scale_d) {
  asm volatile("{\n.reg .pred p;\nsetp.ne.b32 p, %61, 0;\n"
    "wgmma.mma_async.sync.aligned.m64n112k16.f32.bf16.bf16 {%0, %1, %2, %3, %4, %5, %6, %7, %8, %9, %10, %11, %12, %13, %14, %15, %16, %17, %18, %19, %20, %21, %22, %23, %24, %25, %26, %27, %28, %29, %30, %31, %32, %33, %34, %35, %36, %37, %38, %39, %40, %41, %42, %43, %44, %45, %46, %47, %48, %49, %50, %51, %52, %53, %54, %55}, {%56, %57, %58, %59}, %60, p, 1, 1, %62;\n}"
    : "+f"(d[0]), "+f"(d[1]), "+f"(d[2]), "+f"(d[3]), "+f"(d[4]), "+f"(d[5]), "+f"(d[6]), "+f"(d[7]), "+f"(d[8]), "+f"(d[9]), "+f"(d[10]), "+f"(d[11]), "+f"(d[12]), "+f"(d[13]), "+f"(d[14]), "+f"(d[15]), "+f"(d[16]), "+f"(d[17]), "+f"(d[18]), "+f"(d[19]), "+f"(d[20]), "+f"(d[21]), "+f"(d[22]), "+f"(d[23]), "+f"(d[24]), "+f"(d[25]), "+f"(d[26]), "+f"(d[27]), "+f"(d[28]), "+f"(d[29]), "+f"(d[30]), "+f"(d[31]), "+f"(d[32]), "+f"(d[33]), "+f"(d[34]), "+f"(d[35]), "+f"(d[36]), "+f"(d[37]), "+f"(d[38]), "+f"(d[39]), "+f"(d[40]), "+f"(d[41]), "+f"(d[42]), "+f"(d[43]), "+f"(d[44]), "+f"(d[45]), "+f"(d[46]), "+f"(d[47]), "+f"(d[48]), "+f"(d[49]), "+f"(d[50]), "+f"(d[51]), "+f"(d[52]), "+f"(d[53]), "+f"(d[54]), "+f"(d[55])
    : "r"(a0), "r"(a1), "r"(a2), "r"(a3), "l"(db), "r"(scale_d), "n"(TB));
}
template<int TB> __device__ __forceinline__ void wgmma_rs_n32(float (&d)[16], uint32_t a0, uint32_t a1, uint32_t a2, uint32_t a3, uint64_t db, int scale_d) {
  asm volatile("{\n.reg .pred p;\nsetp.ne.b32 p, %21, 0;\n"
    "wgmma.mma_async.sync.aligned.m64n32k16.f32.bf16.bf16 {%0, %1, %2, %3, %4, %5, %6, %7, %8, %9, %10, %11, %12, %13, %14, %15}, {%16, %17, %18, %19}, %20, p, 1, 1, %22;\n}"
    : "+f"(d[0]), "+f"(d[1]), "+f"(d[2]), "+f"(d[3]), "+f"(d[4]), "+f"(d[5]), "+f"(d[6]), "+f"(d[7]), "+f"(d[8]), "+f"(d[9]), "+f"(d[10]), "+f"(d[11]), "+f"(d[12]), "+f"(d[13]), "+f"(d[14]), "+f"(d[15])
    : "r"(a0), "r"(a1), "r"(a2), "r"(a3), "l"(db), "r"(scale_d), "n"(TB));
}


constexpr int A_THREADS = 512;
constexpr int A_CONV_CTAS = 112;
constexpr int A_GRID = 132;
constexpr int A_TBL = 0;
constexpr int A_KACC = 131072;
constexpr int KACC_PITCH = 36;
constexpr int A_KACC_CH = 24 * KACC_PITCH * 4;
constexpr int A_KREV = A_KACC + 4 * A_KACC_CH;
constexpr int KREV_COPY = 4160;
constexpr int A_UPL = A_KREV + 4 * 2 * KREV_COPY;
constexpr int UPL_PAD = 448;
constexpr int UPL_PLANE = 2048 + UPL_PAD;
constexpr int A_XS = A_UPL + 4 * 2 * UPL_PLANE;
constexpr int A_XST = A_XS + 16384;
constexpr int A_SMEM = A_XST + 16384;

struct cplx { float r, i; };
__device__ __forceinline__ cplx cmul(cplx a, cplx b) {
  cplx c;
  c.r = fmaf(a.r, b.r, -a.i * b.i);
  c.i = fmaf(a.r, b.i, a.i * b.r);
  return c;
}
__device__ __forceinline__ cplx cexp_t(float lr2, float rv, float t) {
  float mag = exp2f(lr2 * t);
  float ph = rv * t;
  ph = ph - rintf(ph);
  ph *= 6.283185307179586f;
  cplx c;
  c.r = mag * __cosf(ph);
  c.i = mag * __sinf(ph);
  return c;
}

struct ModeParams { float are, aim, bre, bim, cre, cim; };
__device__ __forceinline__ ModeParams load_mode(const __nv_bfloat16* const* p, int idx) {
  ModeParams m;
  m.are = __bfloat162float(p[0][idx]); m.aim = __bfloat162float(p[1][idx]);
  m.bre = __bfloat162float(p[2][idx]); m.bim = __bfloat162float(p[3][idx]);
  m.cre = __bfloat162float(p[4][idx]); m.cim = __bfloat162float(p[5][idx]);
  return m;
}

__device__ __forceinline__ void kgen_warp(const ModeParams& m, float dt, uint32_t tbl, float* kacc, int lane) {
  const float lr = dt * m.are, li = dt * m.aim;
  const float lr2 = lr * 1.4426950408889634f, rv = li * 0.15915494309189535f;
  const cplx e1 = cexp_t(lr2, rv, 1.f), e8 = cexp_t(lr2, rv, 8.f), e64 = cexp_t(lr2, rv, 64.f), e256 = cexp_t(lr2, rv, 256.f);
  const uint32_t row = (uint32_t)((lane >> 3) * 16 + (lane & 7));
  const uint32_t erow = tbl + row * 80, xrow = tbl + 5120 + row * 48;
  {
    cplx z[8];
    z[0].r = 1.f; z[0].i = 0.f;
    z[1] = e8;
    z[2] = cmul(e8, e8);
    z[3] = cmul(z[2], e8);
    z[4] = cmul(z[2], z[2]);
    z[5] = cmul(z[4], e8);
    z[6] = cmul(z[4], z[2]);
    z[7] = cmul(z[4], z[3]);
#pragma unroll
    for (int g = 0; g < 4; g++) {
      sts128(erow + g * 16, pack_bf16(z[0].r, z[1].r), pack_bf16(z[2].r, z[3].r), pack_bf16(z[4].r, z[5].r), pack_bf16(z[6].r, z[7].r));
      sts128(erow + 8 * 80 + g * 16, pack_bf16(z[0].i, z[1].i), pack_bf16(z[2].i, z[3].i), pack_bf16(z[4].i, z[5].i), pack_bf16(z[6].i, z[7].i));
      if (g < 3) {
        if (g == 0) z[0] = e64; else z[0] = cmul(z[0], e64);
#pragma unroll
        for (int j = 1; j < 8; j++) z[j] = cmul(z[j], e64);
      }
    }
  }
  {
    cplx db; db.r = dt * m.bre; db.i = dt * m.bim;
    cplx c; c.r = m.cre; c.i = m.cim;
    cplx x[8];
    x[0] = cmul(c, db);
    const cplx e2 = cmul(e1, e1), e4 = cmul(e2, e2);
    x[1] = cmul(x[0], e1);
    x[2] = cmul(x[0], e2);
    x[3] = cmul(x[1], e2);
#pragma unroll
    for (int j = 0; j < 4; j++) x[4 + j] = cmul(x[j], e4);
    sts128(xrow, pack_bf16(x[0].r, x[1].r), pack_bf16(x[2].r, x[3].r), pack_bf16(x[4].r, x[5].r), pack_bf16(x[6].r, x[7].r));
    sts128(xrow + 8 * 48, pack_bf16(-x[0].i, -x[1].i), pack_bf16(-x[2].i, -x[3].i), pack_bf16(-x[4].i, -x[5].i), pack_bf16(-x[6].i, -x[7].i));
    cplx y[8];
    y[0] = cmul(x[0], e256); y[1] = cmul(x[2], e256); y[2] = cmul(x[4], e256); y[3] = cmul(x[6], e256);
    y[4] = cmul(y[0], e256); y[5] = cmul(y[2], e256); y[6] = cmul(y[4], e256); y[7] = cmul(y[5], e256);
    sts128(xrow + 16, pack_bf16(y[0].r, y[1].r), pack_bf16(y[2].r, y[3].r), pack_bf16(y[4].r, y[5].r), pack_bf16(y[6].r, y[7].r));
    sts128(xrow + 8 * 48 + 16, pack_bf16(-y[0].i, -y[1].i), pack_bf16(-y[2].i, -y[3].i), pack_bf16(-y[4].i, -y[5].i), pack_bf16(-y[6].i, -y[7].i));
    const cplx e512 = cmul(e256, e256);
    cplx w0 = cmul(y[4], e512);
    cplx w1 = cmul(y[6], e512);
    cplx w2 = cmul(w0, e512);
    cplx w3 = cmul(w1, e512);
    cplx w4 = cmul(w2, e512);
    sts128(xrow + 32, pack_bf16(w0.r, w1.r), pack_bf16(w2.r, w3.r), pack_bf16(w4.r, 0.f), 0u);
    sts128(xrow + 8 * 48 + 32, pack_bf16(-w0.i, -w1.i), pack_bf16(-w2.i, -w3.i), pack_bf16(-w4.i, 0.f), 0u);
  }
  __syncwarp();
  float c[2][3][4];
#pragma unroll
  for (int i = 0; i < 2; i++)
#pragma unroll
    for (int j = 0; j < 3; j++)
#pragma unroll
      for (int k = 0; k < 4; k++) c[i][j][k] = 0.f;
  const int mi = lane >> 3, r8 = lane & 7;
  const uint32_t a_addr = tbl + (uint32_t)((r8 + 8 * (mi >> 1)) * 80 + (mi & 1) * 16);
  const uint32_t b_addr = tbl + 5120 + (uint32_t)((r8 + 8 * (mi & 1)) * 48 + (mi >> 1) * 16);
#pragma unroll
  for (int s = 0; s < 4; s++) {
    uint32_t a[2][4], b[3][2];
    ldsm_x4_t(a[0][0], a[0][1], a[0][2], a[0][3], a_addr + s * 16 * 80);
    ldsm_x4_t(a[1][0], a[1][1], a[1][2], a[1][3], a_addr + s * 16 * 80 + 32);
    ldsm_x4_t(b[0][0], b[0][1], b[1][0], b[1][1], b_addr + s * 16 * 48);
    ldsm_x2_t(b[2][0], b[2][1], b_addr + s * 16 * 48 + 32 - ((mi >> 1) * 16));
#pragma unroll
    for (int i = 0; i < 2; i++)
#pragma unroll
      for (int j = 0; j < 3; j++) mma16816(c[i][j], a[i][0], a[i][1], a[i][2], a[i][3], b[j][0], b[j][1]);
  }
  const int g = lane >> 2, t4 = lane & 3;
#pragma unroll
  for (int i = 0; i < 2; i++)
#pragma unroll
    for (int j = 0; j < 3; j++) {
      float* p = kacc + (8 * j + 2 * t4) * KACC_PITCH + 16 * i + g;
      atomicAdd(p, c[i][j][0]);
      atomicAdd(p + KACC_PITCH, c[i][j][1]);
      atomicAdd(p + 8, c[i][j][2]);
      atomicAdd(p + KACC_PITCH + 8, c[i][j][3]);
    }
  __syncwarp();
}

__device__ __forceinline__ float kval(const float* kacc, int l) {
  if (l < 0) return 0.f;
  int c = (int)__bfloat162float(__float2bfloat16_rn((float)l));
  int a, b;
  if (c < 256) { a = c & 7; b = c >> 3; }
  else if (c < 512) { a = 8 + ((c & 7) >> 1); b = (c - 256) >> 3; }
  else if (c < 1024) { a = 12 + 2 * ((c - 512) >> 8) + ((c >> 2) & 1); b = (c & 255) >> 3; }
  else { a = 16 + ((c - 1024) >> 8); b = (c & 255) >> 3; }
  return kacc[a * KACC_PITCH + b];
}

__device__ __forceinline__ void kexpand_wg(const float* kacc, uint32_t krev, int tid128) {
#pragma unroll 1
  for (int blk = tid128; blk < 260; blk += 128) {
    const int p0 = blk * 8;
    float v[9];
#pragma unroll
    for (int j = 0; j < 9; j++) {
      int l = 2048 - p0 - j;
      v[j] = (l > 2047) ? 0.f : kval(kacc, l);
    }
    sts128(krev + blk * 16, pack_bf16(v[0], v[1]), pack_bf16(v[2], v[3]), pack_bf16(v[4], v[5]), pack_bf16(v[6], v[7]));
    sts128(krev + KREV_COPY + blk * 16, pack_bf16(v[1], v[2]), pack_bf16(v[3], v[4]), pack_bf16(v[5], v[6]), pack_bf16(v[7], v[8]));
  }
}

template <int S>
__device__ __forceinline__ void conv_step(float (&acc)[4][16], uint32_t (&a)[3], uint32_t kaddr, uint64_t d0) {
  uint32_t n0 = 0, n1 = 0, n2 = 0;
  if (S + 1 < 32) {
    const uint32_t ad = kaddr - (uint32_t)((S + 1) * 128);
    n0 = lds32(ad); n1 = lds32(ad - 16); n2 = lds32(ad + 16);
  }
  WG_FENCE();
#pragma unroll
  for (int k = 3; k >= S / 8; k--)
    wgmma_rs_n32<0>(acc[k], a[0], a[1], a[2], a[0], d0 + (uint64_t)(int64_t)(32 * k - 4 * S), S == 0 ? 0 : 1);
  WG_COMMIT();
  WG_WAIT(1);
  a[0] = n0; a[1] = n1; a[2] = n2;
}
template <int S>
struct ConvLoop {
  static __device__ __forceinline__ void run(float (&acc)[4][16], uint32_t (&a)[3], uint32_t kaddr, uint64_t d0) {
    conv_step<S>(acc, a, kaddr, d0);
    ConvLoop<S + 1>::run(acc, a, kaddr, d0);
  }
};
template <>
struct ConvLoop<32> {
  static __device__ __forceinline__ void run(float (&)[4][16], uint32_t (&)[3], uint32_t, uint64_t) {}
};

__device__ __forceinline__ void conv_channel(uint32_t sbase, int ch, int wg, int d, float dskip, int tid128) {
  const int w = tid128 >> 5, lane = tid128 & 31, g = lane >> 2, t4 = lane & 3;
  float acc[4][16];
  const uint32_t krev = sbase + A_KREV + ch * 2 * KREV_COPY;
  const uint32_t kaddr = (g & 1) ? (krev + KREV_COPY + 2 * (2047 - 16 * w - g + 2 * t4)) : (krev + 2 * (2048 - 16 * w - g + 2 * t4));
  const uint32_t upl = sbase + A_UPL + ch * 2 * UPL_PLANE + UPL_PAD;
  const uint64_t d0 = mkdesc(upl, UPL_PLANE, 128, 0);
  uint32_t a[3];
  a[0] = lds32(kaddr); a[1] = lds32(kaddr - 16); a[2] = lds32(kaddr + 16);
  ConvLoop<0>::run(acc, a, kaddr, d0);
  WG_WAIT(0);
  const uint32_t buf = sbase + A_TBL + wg * 32768;
  {
    const uint32_t wb = buf + w * 8192;
    if (lane < 4 * w) sts128(wb + (uint32_t)((lane * 4) ^ ((((lane * 4) >> 5) & 3) << 3)) * 4, 0u, 0u, 0u, 0u);
#pragma unroll
    for (int j = 0; j < 16; j++)
#pragma unroll
      for (int e = 0; e < 4; e++) {
        const int t = 16 * (8 * j + 2 * t4 + (e & 1) + w) + g + 8 * (e >> 1);
        if (j < 15 || t < 2048) {
          const int ts = t ^ (((t >> 5) & 3) << 3);
          asm volatile("st.shared.f32 [%0], %1;" ::"r"(wb + ts * 4), "f"(acc[j >> 2][4 * (j & 3) + e]) : "memory");
        }
      }
  }
  bar_sync(3 + wg, 128);
  const uint32_t xs = sbase + A_XS + ch * 4096;
  __nv_bfloat16* hrow = g_hT + (size_t)d * L_;
#pragma unroll
  for (int k = 0; k < 4; k++) {
    const int t = 4 * tid128 + 512 * k;
    const int ts = t ^ (((t >> 5) & 3) << 3);
    float y[4] = {0.f, 0.f, 0.f, 0.f};
#pragma unroll
    for (int ww = 0; ww < 4; ww++) {
      uint4 v = lds128(buf + ww * 8192 + ts * 4);
      y[0] += __uint_as_float(v.x); y[1] += __uint_as_float(v.y); y[2] += __uint_as_float(v.z); y[3] += __uint_as_float(v.w);
    }
    uint2 uu = lds64(upl + ((t >> 3) & 1) * UPL_PLANE + (t >> 4) * 16 + (t & 7) * 2);
    uint2 xx = lds64(xs + t * 2);
    float uf[4] = {bf_lo(uu.x), bf_hi(uu.x), bf_lo(uu.y), bf_hi(uu.y)};
    float xf[4] = {bf_lo(xx.x), bf_hi(xx.x), bf_lo(xx.y), bf_hi(xx.y)};
    float h[4];
#pragma unroll
    for (int i = 0; i < 4; i++) h[i] = xf[i] + bf_round(bf_round(y[i]) + bf_round(uf[i] * dskip));
    uint2 o;
    o.x = pack_bf16(h[0], h[1]);
    o.y = pack_bf16(h[2], h[3]);
    *reinterpret_cast<uint2*>(hrow + t) = o;
  }
}

__device__ __forceinline__ uint32_t row_stats(const __nv_bfloat16* __restrict__ xrow, int lane) {
  uint32_t v[7];
#pragma unroll
  for (int j = 0; j < 7; j++) v[j] = reinterpret_cast<const uint32_t*>(xrow)[lane + 32 * j];
  float s = 0.f;
#pragma unroll
  for (int j = 0; j < 7; j++) s += bf_lo(v[j]) + bf_hi(v[j]);
#pragma unroll
  for (int o = 16; o; o >>= 1) s += __shfl_xor_sync(0xffffffffu, s, o);
  const float mean = s * (1.f / D_);
  float q = 0.f;
#pragma unroll
  for (int j = 0; j < 7; j++) {
    float a = bf_lo(v[j]) - mean, b = bf_hi(v[j]) - mean;
    q = fmaf(a, a, q);
    q = fmaf(b, b, q);
  }
#pragma unroll
  for (int o = 16; o; o >>= 1) q += __shfl_xor_sync(0xffffffffu, q, o);
  const float var = bf_round(q * (1.f / D_));
  const float den = sqrtf(bf_round(var + 1e-5f));
  return pack_bf16(mean, den);
}

struct AParams {
  const __nv_bfloat16* x;
  const __nv_bfloat16* p[6];
  const __nv_bfloat16* log_dt;
  const __nv_bfloat16* dskip;
  const __nv_bfloat16* wg;
  const __nv_bfloat16* wu;
  const __nv_bfloat16* wd;
};

__global__ void __launch_bounds__(A_THREADS, 1) s4_conv_kernel(const AParams P) {
  extern __shared__ __align__(1024) unsigned char smem[];
  const int tid = threadIdx.x, warp = __shfl_sync(0xffffffffu, tid >> 5, 0), lane = tid & 31, wg = warp >> 2, tid128 = tid & 127;
  const uint32_t sbase = smem_u32(smem);
  asm volatile("griddepcontrol.launch_dependents;");
  const bool is_conv = blockIdx.x < A_CONV_CTAS;
  const int d0 = blockIdx.x * 4;
  ModeParams mp;
  float dt_a = 0.f;
  if (is_conv) {
#pragma unroll
    for (int j = 0; j < 4; j++) {
      const int t = tid + 512 * j;
      asm volatile("cp.async.ca.shared.global [%0], [%1], 8;" ::"r"(sbase + A_XST + t * 8), "l"(P.x + (size_t)t * D_ + d0) : "memory");
    }
    asm volatile("cp.async.commit_group;" ::: "memory");
    mp = load_mode(P.p, (d0 + (warp >> 3)) * NM_ + (warp & 7) * 32 + lane);
    dt_a = __bfloat162float(P.log_dt[d0 + (warp >> 3)]);
  }
  if (blockIdx.x < 128) {
    const int t = blockIdx.x * 16 + warp;
    const uint32_t st = row_stats(P.x + (size_t)t * D_, lane);
    if (lane == 0) asm volatile("st.relaxed.gpu.global.u32 [%0], %1;" ::"l"(g_stats + t), "r"(st) : "memory");
  }
  if (!is_conv) {
    const int hb = blockIdx.x - A_CONV_CTAS;
    if (hb == 19) {
      for (int i = tid; i < 16 * 8 * 8 * 2; i += A_THREADS) g_flags[i] = 0u;
    }
    {
      for (int i = hb * A_THREADS + tid; i < F_ * D_ * 2 / 128; i += 20 * A_THREADS)
        asm volatile("prefetch.global.L2 [%0];" ::"l"((const char*)P.wd + (size_t)i * 128));
    }
    float* red = reinterpret_cast<float*>(smem);
    const int cc = lane & 7, rg = tid >> 3;
    uint4 v[3][7];
#pragma unroll
    for (int k = 0; k < 3; k++) {
      const int unit = hb + 20 * k;
      if (unit < 56) {
        const __nv_bfloat16* W = (unit < 28) ? P.wg : P.wu;
        const int col = (unit % 28) * 64 + cc * 8;
#pragma unroll
        for (int j = 0; j < 7; j++) v[k][j] = __ldg(reinterpret_cast<const uint4*>(W + (size_t)(rg + 64 * j) * F_ + col));
      }
    }
#pragma unroll
    for (int k = 0; k < 3; k++) {
      const int unit = hb + 20 * k;
      if (unit < 56) {
        float s[8];
#pragma unroll
        for (int i = 0; i < 8; i++) s[i] = 0.f;
#pragma unroll
        for (int j = 0; j < 7; j++) {
          s[0] += bf_lo(v[k][j].x); s[1] += bf_hi(v[k][j].x); s[2] += bf_lo(v[k][j].y); s[3] += bf_hi(v[k][j].y);
          s[4] += bf_lo(v[k][j].z); s[5] += bf_hi(v[k][j].z); s[6] += bf_lo(v[k][j].w); s[7] += bf_hi(v[k][j].w);
        }
#pragma unroll
        for (int i = 0; i < 8; i++) {
          s[i] += __shfl_xor_sync(0xffffffffu, s[i], 8);
          s[i] += __shfl_xor_sync(0xffffffffu, s[i], 16);
        }
        __syncthreads();
        if (lane < 8) {
#pragma unroll
          for (int i = 0; i < 8; i++) red[warp * 64 + lane * 8 + i] = s[i];
        }
        __syncthreads();
        if (tid < 64) {
          float a = 0.f;
#pragma unroll
          for (int w = 0; w < 16; w++) a += red[w * 64 + tid];
          g_csum[unit * 64 + tid] = a;
        }
      }
    }
    return;
  }
  float* kacc_all = reinterpret_cast<float*>(smem + A_KACC);
  for (int i = tid; i < 4 * 24 * KACC_PITCH; i += A_THREADS) kacc_all[i] = 0.f;
  ModeParams mp2a, mp2b;
  float dt_b = 0.f;
  if (wg >= 2) {
    mp2a = load_mode(P.p, (d0 + wg) * NM_ + (warp & 3) * 32 + lane);
    mp2b = load_mode(P.p, (d0 + wg) * NM_ + 128 + (warp & 3) * 32 + lane);
    dt_b = __bfloat162float(P.log_dt[d0 + wg]);
  }
  const float dskip = __bfloat162float(P.dskip[d0 + wg]);
  __syncthreads();
  kgen_warp(mp, bf_round(__expf(dt_a)), sbase + A_TBL + warp * 8192, kacc_all + (warp >> 3) * 24 * KACC_PITCH, lane);
  asm volatile("cp.async.wait_group 0;" ::: "memory");
  __syncthreads();
  if (wg < 2) {
    kexpand_wg(kacc_all + wg * 24 * KACC_PITCH, sbase + A_KREV + wg * 2 * KREV_COPY, tid128);
    {
      const int t0 = tid * 8;
      uint32_t st[8];
      int it = 0;
      while (true) {
        asm volatile("ld.relaxed.gpu.global.v4.u32 {%0,%1,%2,%3}, [%4];" : "=r"(st[0]), "=r"(st[1]), "=r"(st[2]), "=r"(st[3]) : "l"(g_stats + t0) : "memory");
        asm volatile("ld.relaxed.gpu.global.v4.u32 {%0,%1,%2,%3}, [%4];" : "=r"(st[4]), "=r"(st[5]), "=r"(st[6]), "=r"(st[7]) : "l"(g_stats + t0 + 4) : "memory");
        bool ok = true;
#pragma unroll
        for (int i = 0; i < 8; i++) ok = ok && (st[i] != 0u);
        if (ok) break;
        if (++it > (1 << 20)) break;
      }
      uint4 xv[4];
#pragma unroll
      for (int i = 0; i < 4; i++) xv[i] = lds128(sbase + A_XST + t0 * 8 + i * 16);
      float xf[8][4], uf[8][4];
#pragma unroll
      for (int i = 0; i < 4; i++) {
        xf[2 * i][0] = bf_lo(xv[i].x); xf[2 * i][1] = bf_hi(xv[i].x); xf[2 * i][2] = bf_lo(xv[i].y); xf[2 * i][3] = bf_hi(xv[i].y);
        xf[2 * i + 1][0] = bf_lo(xv[i].z); xf[2 * i + 1][1] = bf_hi(xv[i].z); xf[2 * i + 1][2] = bf_lo(xv[i].w); xf[2 * i + 1][3] = bf_hi(xv[i].w);
      }
#pragma unroll
      for (int i = 0; i < 8; i++) {
        const float m = bf_lo(st[i]), den = bf_hi(st[i]);
#pragma unroll
        for (int c = 0; c < 4; c++) uf[i][c] = __fdiv_rn(bf_round(xf[i][c] - m), den);
      }
#pragma unroll
      for (int c = 0; c < 4; c++) {
        sts128(sbase + A_UPL + c * 2 * UPL_PLANE + UPL_PAD + (tid & 1) * UPL_PLANE + (tid >> 1) * 16,
               pack_bf16(uf[0][c], uf[1][c]), pack_bf16(uf[2][c], uf[3][c]), pack_bf16(uf[4][c], uf[5][c]), pack_bf16(uf[6][c], uf[7][c]));
        sts128(sbase + A_XS + c * 4096 + t0 * 2,
               pack_bf16(xf[0][c], xf[1][c]), pack_bf16(xf[2][c], xf[3][c]), pack_bf16(xf[4][c], xf[5][c]), pack_bf16(xf[6][c], xf[7][c]));
      }
      if (tid < 8 * 28) sts128(sbase + A_UPL + (tid / 28) * UPL_PLANE + (tid % 28) * 16, 0u, 0u, 0u, 0u);
      fence_proxy_async();
    }
    bar_arrive(2, 512);
    bar_sync(1, 256);
    conv_channel(sbase, wg, wg, d0 + wg, dskip, tid128);
  } else {
    const float dt = bf_round(__expf(dt_b));
    kgen_warp(mp2a, dt, sbase + A_TBL + warp * 8192, kacc_all + wg * 24 * KACC_PITCH, lane);
    kgen_warp(mp2b, dt, sbase + A_TBL + warp * 8192, kacc_all + wg * 24 * KACC_PITCH, lane);
    bar_sync(3 + wg, 128);
    kexpand_wg(kacc_all + wg * 24 * KACC_PITCH, sbase + A_KREV + wg * 2 * KREV_COPY, tid128);
    bar_sync(2, 512);
    conv_channel(sbase, wg, wg, d0 + wg, dskip, tid128);
  }
}

constexpr int B_THREADS = 384;
constexpr int B_HT = 0;
constexpr int B_RING = 114688;
constexpr int NSLOT = 7;
constexpr int B_CS = B_RING + NSLOT * 16384;
constexpr int B_RS = B_CS + 448 * 4;
constexpr int B_BAR = B_RS + 128 * 8;
constexpr int B_SMEM = B_BAR + 32 * 8;
constexpr int BAR_FULL = 0, BAR_EMPTY = 7, BAR_H = 14, BAR_XFREE = 21, BAR_X = 23;

__device__ __forceinline__ float glu_act(float g, float u) {
  return __fdividef(u, 1.f + __expf(-g));
}
__device__ __forceinline__ void glu_block(const float* ag, const float* au, float2 cg, float2 cu, float2 s0, float2 s1, uint32_t& o0, uint32_t& o1) {
  const float g0 = fmaf(ag[0], s0.x, s0.y * cg.x), g1 = fmaf(ag[1], s0.x, s0.y * cg.y);
  const float u0 = fmaf(au[0], s0.x, s0.y * cu.x), u1 = fmaf(au[1], s0.x, s0.y * cu.y);
  const float g2 = fmaf(ag[2], s1.x, s1.y * cg.x), g3 = fmaf(ag[3], s1.x, s1.y * cg.y);
  const float u2 = fmaf(au[2], s1.x, s1.y * cu.x), u3 = fmaf(au[3], s1.x, s1.y * cu.y);
  o0 = pack_bf16(glu_act(g0, u0), glu_act(g1, u1));
  o1 = pack_bf16(glu_act(g2, u2), glu_act(g3, u3));
}
__device__ __forceinline__ void wait_flag(const uint32_t* f, int lane) {
  if (lane == 0) {
    uint32_t v;
    int it = 0;
    do {
      asm volatile("ld.acquire.gpu.global.u32 %0, [%1];" : "=r"(v) : "l"(f) : "memory");
      if (++it > (1 << 20)) break;
    } while (v == 0u);
  }
  __syncwarp();
}
__device__ __forceinline__ uint4 ldg_relaxed(const uint4* p) {
  uint4 r;
  asm volatile("ld.relaxed.gpu.global.v4.u32 {%0,%1,%2,%3}, [%4];" : "=r"(r.x), "=r"(r.y), "=r"(r.z), "=r"(r.w) : "l"(p) : "memory");
  return r;
}

template <int U0, int NK>
__device__ __forceinline__ void g2_group(float (&acc)[56], const uint4 (&fr)[NK], uint32_t sbase, bool elect) {
#pragma unroll
  for (int k = 0; k < NK; k += 2) {
    constexpr int dummy = 0; (void)dummy;
    const int u = U0 + k / 2;
    const int fill = 28 + u / 2, slot = fill % NSLOT;
    if ((u & 1) == 0) mbar_wait(sbase + B_BAR + (BAR_FULL + slot) * 8, (fill / NSLOT) & 1);
    const uint32_t bb = sbase + B_RING + slot * 16384 + (u & 1) * 8192;
    WG_FENCE();
    wgmma_rs_n112<1>(acc, fr[k].x, fr[k].y, fr[k].z, fr[k].w, mkdesc(bb, 4096, 1024, 1), u == 0 ? 0 : 1);
    wgmma_rs_n112<1>(acc, fr[k + 1].x, fr[k + 1].y, fr[k + 1].z, fr[k + 1].w, mkdesc(bb + 2048, 4096, 1024, 1), 1);
    WG_COMMIT();
    WG_WAIT(1);
    if (u >= 2 && (u & 1) == 0) {
      const int pf = 28 + (u - 1) / 2;
      if (elect) mbar_arrive(sbase + B_BAR + (BAR_EMPTY + pf % NSLOT) * 8);
    }
  }
}

__global__ void __cluster_dims__(2, 1, 1) __launch_bounds__(B_THREADS, 1)
glu_kernel(const __grid_constant__ CUtensorMap tm_h, const __grid_constant__ CUtensorMap tm_wg, const __grid_constant__ CUtensorMap tm_wu,
           const __grid_constant__ CUtensorMap tm_wg32, const __grid_constant__ CUtensorMap tm_wu32, const __grid_constant__ CUtensorMap tm_wd,
           __nv_bfloat16* __restrict__ out) {
  extern __shared__ __align__(1024) unsigned char smem[];
  const int tid = threadIdx.x, warp = __shfl_sync(0xffffffffu, tid >> 5, 0), lane = tid & 31;
  const uint32_t sbase = smem_u32(smem);
  const int rt = blockIdx.x >> 3, q = (blockIdx.x >> 1) & 3, rank = blockIdx.x & 1;
  const int slice = rank * 4 + q;
  const int f0 = slice * 224;
  const uint32_t bars = sbase + B_BAR;
  if (tid == 0) {
    if (sbase & 1023) __trap();
    for (int i = 0; i < NSLOT; i++) {
      mbar_init(bars + (BAR_FULL + i) * 8, 1);
      mbar_init(bars + (BAR_EMPTY + i) * 8, 2);
      mbar_init(bars + (BAR_H + i) * 8, 1);
    }
    for (int i = 0; i < 2; i++) {
      mbar_init(bars + (BAR_XFREE + i) * 8, 1);
      mbar_init(bars + (BAR_X + i) * 8, 1);
    }
    asm volatile("fence.mbarrier_init.release.cluster;" ::: "memory");
    mbar_expect_tx(bars + (BAR_X + 0) * 8, 128 * 7 * 16);
    mbar_expect_tx(bars + (BAR_X + 1) * 8, 128 * 7 * 16);
  }
  if (tid >= 256 && tid < 384) {
    float* rs = reinterpret_cast<float*>(smem + B_RS);
    rs[tid - 256] = 0.f;
    rs[tid - 128] = 0.f;
  }
  __syncthreads();
  asm volatile("barrier.cluster.arrive.release.aligned;\nbarrier.cluster.wait.acquire.aligned;" ::: "memory");

  if (warp >= 8) {
    asm volatile("setmaxnreg.dec.sync.aligned.u32 56;");
    if (warp == 8) {
      if (lane == 0) {
#pragma unroll 1
        for (int fill = 0; fill < 42; fill++) {
          const int slot = fill % NSLOT;
          const uint32_t fb = bars + (BAR_FULL + slot) * 8;
          const uint32_t dst = sbase + B_RING + slot * 16384;
          if (fill == NSLOT) {
            asm volatile("griddepcontrol.wait;" ::: "memory");
#pragma unroll 1
            for (int c = 0; c < 7; c++) {
              const uint32_t hb = bars + (BAR_H + c) * 8;
              mbar_expect_tx(hb, 16384);
              tma_load_2d(sbase + B_HT + c * 8192, &tm_h, rt * 128, c * 64, hb);
              tma_load_2d(sbase + B_HT + (7 + c) * 8192, &tm_h, rt * 128 + 64, c * 64, hb);
            }
          }
          if (fill >= NSLOT) mbar_wait(bars + (BAR_EMPTY + slot) * 8, ((fill / NSLOT) - 1) & 1);
          if (fill < 14) {
            const int k = fill * 32;
            mbar_expect_tx(fb, 16384);
            tma_load_2d(dst, &tm_wg, f0, k, fb);
            tma_load_2d(dst + 4096, &tm_wg, f0 + 64, k, fb);
            tma_load_2d(dst + 8192, &tm_wu, f0, k, fb);
            tma_load_2d(dst + 12288, &tm_wu, f0 + 64, k, fb);
          } else if (fill < 28) {
            const int k = (fill - 14) * 32;
            mbar_expect_tx(fb, 12288);
            tma_load_2d(dst, &tm_wg, f0 + 128, k, fb);
            tma_load_2d(dst + 4096, &tm_wu, f0 + 128, k, fb);
            tma_load_2d(dst + 8192, &tm_wg32, f0 + 192, k, fb);
            tma_load_2d(dst + 10240, &tm_wu32, f0 + 192, k, fb);
          } else {
            mbar_expect_tx(fb, 16384);
#pragma unroll
            for (int hh = 0; hh < 2; hh++) {
              const int u = (fill - 28) * 2 + hh;
              int fr;
              if (u < 7) fr = f0 + u * 32;
              else if (u < 19) fr = (rank * 4 + ((q + 1 + (u - 7) / 4) & 3)) * 224 + ((u - 7) & 3) * 32;
              else fr = (rank * 4 + ((q + 1 + (u - 19) / 3) & 3)) * 224 + 128 + ((u - 19) % 3) * 32;
              tma_load_2d(dst + hh * 8192, &tm_wd, q * 112, fr, fb);
              tma_load_2d(dst + hh * 8192 + 4096, &tm_wd, q * 112 + 64, fr, fb);
            }
          }
        }
      }
    } else {
      const int st = tid - 288;
      asm volatile("griddepcontrol.wait;" ::: "memory");
      float* cs = reinterpret_cast<float*>(smem + B_CS);
      for (int i = st; i < 448; i += 96) cs[i] = (i < 224) ? g_csum[f0 + i] : g_csum[F_ + f0 + i - 224];
      if (st < 16) g_stats[blockIdx.x * 16 + st] = 0u;
      const int tc = st & 15, rg = st >> 4;
      const uint32_t hb = sbase + B_HT + (tc >> 3) * 7 * 8192;
      float s1[8], s2[8], sh[8];
#pragma unroll
      for (int i = 0; i < 8; i++) { s1[i] = 0.f; s2[i] = 0.f; }
      mbar_wait(bars + (BAR_H + 0) * 8, 0);
      {
        uint4 v = lds128(hb + ((tc & 7) << 4));
        sh[0] = bf_lo(v.x); sh[1] = bf_hi(v.x); sh[2] = bf_lo(v.y); sh[3] = bf_hi(v.y);
        sh[4] = bf_lo(v.z); sh[5] = bf_hi(v.z); sh[6] = bf_lo(v.w); sh[7] = bf_hi(v.w);
      }
#pragma unroll 1
      for (int c = 0; c < 7; c++) {
        mbar_wait(bars + (BAR_H + c) * 8, 0);
#pragma unroll 2
        for (int r = rg; r < 64; r += 6) {
          uint4 v = lds128(hb + c * 8192 + r * 128 + (((tc & 7) ^ (r & 7)) << 4));
          float f[8] = {bf_lo(v.x), bf_hi(v.x), bf_lo(v.y), bf_hi(v.y), bf_lo(v.z), bf_hi(v.z), bf_lo(v.w), bf_hi(v.w)};
#pragma unroll
          for (int i = 0; i < 8; i++) {
            const float a = f[i] - sh[i];
            s1[i] += a;
            s2[i] = fmaf(a, a, s2[i]);
          }
        }
      }
      float* rs = reinterpret_cast<float*>(smem + B_RS);
#pragma unroll
      for (int i = 0; i < 8; i++) {
        s1[i] += __shfl_xor_sync(0xffffffffu, s1[i], 16);
        s2[i] += __shfl_xor_sync(0xffffffffu, s2[i], 16);
      }
      if (lane < 16) {
#pragma unroll
        for (int i = 0; i < 8; i++) {
          atomicAdd(rs + (tc * 8 + i) * 2, s1[i]);
          atomicAdd(rs + (tc * 8 + i) * 2 + 1, s2[i]);
        }
      }
      bar_sync(2, 96);
      if (st < 16) {
#pragma unroll
        for (int i = 0; i < 8; i++) {
          const float a = rs[(tc * 8 + i) * 2] * (1.f / D_), b = rs[(tc * 8 + i) * 2 + 1] * (1.f / D_);
          const float mean = bf_round(sh[i] + a);
          const float var = bf_round(fmaxf(b - a * a, 0.f));
          const float den = bf_round(sqrtf(bf_round(var + 1e-5f)));
          const float r = 1.f / den;
          rs[(tc * 8 + i) * 2] = r;
          rs[(tc * 8 + i) * 2 + 1] = -mean * r;
        }
      }
      bar_arrive(1, 256 + 96);
    }
  } else {
    asm volatile("setmaxnreg.inc.sync.aligned.u32 224;");
    const int w = warp >> 2, wq = warp & 3, g = lane >> 2, t4 = lane & 3;
    const bool elect = (tid & 127) == 0;
    const uint32_t ht = sbase + B_HT + w * 7 * 8192;
    uint4 H1[8], H2[6];
    uint4* hout = g_H + ((size_t)((rt * 8 + slice) * 8 + warp) * 14) * 32 + lane;
    uint32_t* myflag = g_flags + ((rt * 8 + slice) * 8 + warp) * 2;
    const float* cs = reinterpret_cast<const float*>(smem + B_CS);
    float2 s0, s1;
    {
      float acc[128];
#pragma unroll 1
      for (int u = 0; u < 14; u++) {
        const int slot = u % NSLOT;
        if ((u & 1) == 0) mbar_wait(bars + (BAR_H + (u >> 1)) * 8, 0);
        mbar_wait(bars + (BAR_FULL + slot) * 8, (u / NSLOT) & 1);
        const uint32_t aa = ht + u * 4096, bb = sbase + B_RING + slot * 16384;
        WG_FENCE();
        wgmma_ss_n256<1, 1>(acc, mkdesc(aa, 8192, 1024, 1), mkdesc(bb, 4096, 1024, 1), u > 0);
        wgmma_ss_n256<1, 1>(acc, mkdesc(aa + 2048, 8192, 1024, 1), mkdesc(bb + 2048, 4096, 1024, 1), 1);
        WG_COMMIT();
        WG_WAIT(1);
        if (u > 0 && elect) mbar_arrive(bars + (BAR_EMPTY + (u - 1) % NSLOT) * 8);
      }
      WG_WAIT(0);
      if (elect) mbar_arrive(bars + (BAR_EMPTY + 13 % NSLOT) * 8);
      bar_sync(1, 256 + 96);
      {
        const float2* rs = reinterpret_cast<const float2*>(smem + B_RS);
        s0 = rs[w * 64 + wq * 16 + g];
        s1 = rs[w * 64 + wq * 16 + g + 8];
      }
#pragma unroll
      for (int kb = 0; kb < 8; kb++) {
        const float2 cg0 = *reinterpret_cast<const float2*>(cs + 16 * kb + 2 * t4), cg1 = *reinterpret_cast<const float2*>(cs + 16 * kb + 8 + 2 * t4);
        const float2 cu0 = *reinterpret_cast<const float2*>(cs + 224 + 16 * kb + 2 * t4), cu1 = *reinterpret_cast<const float2*>(cs + 224 + 16 * kb + 8 + 2 * t4);
        glu_block(&acc[8 * kb], &acc[64 + 8 * kb], cg0, cu0, s0, s1, H1[kb].x, H1[kb].y);
        glu_block(&acc[8 * kb + 4], &acc[64 + 8 * kb + 4], cg1, cu1, s0, s1, H1[kb].z, H1[kb].w);
        hout[kb * 32] = H1[kb];
      }
    }
    {
      float accA[64], accB[32];
#pragma unroll 1
      for (int u = 0; u < 14; u++) {
        const int fill = 14 + u, slot = fill % NSLOT;
        mbar_wait(bars + (BAR_FULL + slot) * 8, (fill / NSLOT) & 1);
        const uint32_t aa = ht + u * 4096, bb = sbase + B_RING + slot * 16384;
        WG_FENCE();
        wgmma_ss_n128<1, 1>(accA, mkdesc(aa, 8192, 1024, 1), mkdesc(bb, 4096, 1024, 1), u > 0);
        wgmma_ss_n64<1, 1>(accB, mkdesc(aa, 8192, 1024, 1), mkdesc(bb + 8192, 2048, 512, 2), u > 0);
        wgmma_ss_n128<1, 1>(accA, mkdesc(aa + 2048, 8192, 1024, 1), mkdesc(bb + 2048, 4096, 1024, 1), 1);
        wgmma_ss_n64<1, 1>(accB, mkdesc(aa + 2048, 8192, 1024, 1), mkdesc(bb + 8192 + 1024, 2048, 512, 2), 1);
        WG_COMMIT();
        if (u == 0) {
          __syncwarp();
          if (lane == 0) asm volatile("fence.acq_rel.gpu;\nst.relaxed.gpu.global.u32 [%0], 1;" ::"l"(myflag) : "memory");
          __syncwarp();
        }
        WG_WAIT(1);
        if (u > 0 && elect) mbar_arrive(bars + (BAR_EMPTY + (fill - 1) % NSLOT) * 8);
      }
      WG_WAIT(0);
      if (elect) {
        mbar_arrive(bars + (BAR_EMPTY + 27 % NSLOT) * 8);
      }
#pragma unroll
      for (int kb = 0; kb < 4; kb++) {
        const int c = 128 + 16 * kb;
        const float2 cg0 = *reinterpret_cast<const float2*>(cs + c + 2 * t4), cg1 = *reinterpret_cast<const float2*>(cs + c + 8 + 2 * t4);
        const float2 cu0 = *reinterpret_cast<const float2*>(cs + 224 + c + 2 * t4), cu1 = *reinterpret_cast<const float2*>(cs + 224 + c + 8 + 2 * t4);
        glu_block(&accA[8 * kb], &accA[32 + 8 * kb], cg0, cu0, s0, s1, H2[kb].x, H2[kb].y);
        glu_block(&accA[8 * kb + 4], &accA[32 + 8 * kb + 4], cg1, cu1, s0, s1, H2[kb].z, H2[kb].w);
        hout[(8 + kb) * 32] = H2[kb];
      }
#pragma unroll
      for (int kb = 0; kb < 2; kb++) {
        const int c = 192 + 16 * kb;
        const float2 cg0 = *reinterpret_cast<const float2*>(cs + c + 2 * t4), cg1 = *reinterpret_cast<const float2*>(cs + c + 8 + 2 * t4);
        const float2 cu0 = *reinterpret_cast<const float2*>(cs + 224 + c + 2 * t4), cu1 = *reinterpret_cast<const float2*>(cs + 224 + c + 8 + 2 * t4);
        glu_block(&accB[8 * kb], &accB[16 + 8 * kb], cg0, cu0, s0, s1, H2[4 + kb].x, H2[4 + kb].y);
        glu_block(&accB[8 * kb + 4], &accB[16 + 8 * kb + 4], cg1, cu1, s0, s1, H2[4 + kb].z, H2[4 + kb].w);
        hout[(12 + kb) * 32] = H2[4 + kb];
      }
    }
    bar_sync(3 + w, 128);
    if (elect) {
      uint32_t rb;
      asm volatile("mapa.shared::cluster.u32 %0, %1, %2;" : "=r"(rb) : "r"(bars + (BAR_XFREE + w) * 8), "r"(rank ^ 1));
      mbar_arrive_remote(rb);
    }
    __syncwarp();
    if (lane == 0) asm volatile("fence.acq_rel.gpu;\nst.relaxed.gpu.global.u32 [%0], 1;" ::"l"(myflag + 1) : "memory");
    __syncwarp();
    float acc[56];
    {
      const uint4* hsrc[3];
      const uint32_t* fsrc[3];
#pragma unroll
      for (int j = 0; j < 3; j++) {
        const int s = rank * 4 + ((q + 1 + j) & 3);
        hsrc[j] = g_H + ((size_t)((rt * 8 + s) * 8 + warp) * 14) * 32 + lane;
        fsrc[j] = g_flags + ((rt * 8 + s) * 8 + warp) * 2;
      }
      uint4 Fa[8], Fb[8], Fc[8];
      uint4 Ga[6], Gb[6], Gc[6];
      wait_flag(fsrc[0], lane);
#pragma unroll
      for (int k = 0; k < 8; k++) Fa[k] = ldg_relaxed(hsrc[0] + k * 32);
      wait_flag(fsrc[1], lane);
#pragma unroll
      for (int k = 0; k < 8; k++) Fb[k] = ldg_relaxed(hsrc[1] + k * 32);
      g2_group<0, 8>(acc, H1, sbase, elect);
      g2_group<4, 6>(acc, H2, sbase, elect);
      wait_flag(fsrc[2], lane);
#pragma unroll
      for (int k = 0; k < 8; k++) Fc[k] = ldg_relaxed(hsrc[2] + k * 32);
      g2_group<7, 8>(acc, Fa, sbase, elect);
      wait_flag(fsrc[0] + 1, lane);
#pragma unroll
      for (int k = 0; k < 6; k++) Ga[k] = ldg_relaxed(hsrc[0] + (8 + k) * 32);
      g2_group<11, 8>(acc, Fb, sbase, elect);
      wait_flag(fsrc[1] + 1, lane);
#pragma unroll
      for (int k = 0; k < 6; k++) Gb[k] = ldg_relaxed(hsrc[1] + (8 + k) * 32);
      g2_group<15, 8>(acc, Fc, sbase, elect);
      wait_flag(fsrc[2] + 1, lane);
#pragma unroll
      for (int k = 0; k < 6; k++) Gc[k] = ldg_relaxed(hsrc[2] + (8 + k) * 32);
      g2_group<19, 6>(acc, Ga, sbase, elect);
      g2_group<22, 6>(acc, Gb, sbase, elect);
      g2_group<25, 6>(acc, Gc, sbase, elect);
      WG_WAIT(0);
    }
    {
      const int peer = rank ^ 1;
      const int c0p = (112 * q + 56 * peer) >> 6, c0m = (112 * q + 56 * rank) >> 6;
      const int tid128 = tid & 127;
      uint32_t dA = ht + ((c0p + 2) % 7) * 8192 + tid128 * 16, dB = ht + ((c0p + 3) % 7) * 8192 + tid128 * 16, rbar;
      asm volatile("mapa.shared::cluster.u32 %0, %1, %2;" : "=r"(dA) : "r"(dA), "r"(peer));
      asm volatile("mapa.shared::cluster.u32 %0, %1, %2;" : "=r"(dB) : "r"(dB), "r"(peer));
      asm volatile("mapa.shared::cluster.u32 %0, %1, %2;" : "=r"(rbar) : "r"(bars + (BAR_X + w) * 8), "r"(peer));
      float keep[28];
      mbar_wait_cluster(bars + (BAR_XFREE + w) * 8, 0);
#pragma unroll
      for (int j = 0; j < 7; j++) {
        float sv[4];
#pragma unroll
        for (int e = 0; e < 4; e++) {
          sv[e] = rank ? acc[4 * j + e] : acc[28 + 4 * j + e];
          keep[4 * j + e] = rank ? acc[28 + 4 * j + e] : acc[4 * j + e];
        }
        const uint32_t da = (j < 4) ? dA + j * 2048 : dB + (j - 4) * 2048;
        asm volatile("st.async.weak.shared::cluster.mbarrier::complete_tx::bytes.v4.f32 [%0], {%1,%2,%3,%4}, [%5];"
                     ::"r"(da), "f"(sv[0]), "f"(sv[1]), "f"(sv[2]), "f"(sv[3]), "r"(rbar) : "memory");
      }
      uint32_t hr[7][2];
      const int dbase = 112 * q + 56 * rank;
      {
        const int mi = lane >> 3, r8 = lane & 7;
#pragma unroll
        for (int j = 0; j < 8; j += 2) {
          const int jj = j + (mi >> 1);
          const int dd = dbase + 8 * (jj < 7 ? jj : 6) + r8;
          const uint32_t ad = ht + (dd >> 6) * 8192 + (dd & 63) * 128 + (((2 * wq + (mi & 1)) ^ r8) << 4);
          uint32_t r0, r1, r2, r3;
          ldsm_x4_t(r0, r1, r2, r3, ad);
          hr[j][0] = r0; hr[j][1] = r1;
          if (j + 1 < 7) { hr[j + 1][0] = r2; hr[j + 1][1] = r3; }
        }
      }
      mbar_wait_cluster(bars + (BAR_X + w) * 8, 0);
      const uint32_t sA = ht + ((c0m + 2) % 7) * 8192 + tid128 * 16, sB = ht + ((c0m + 3) % 7) * 8192 + tid128 * 16;
      const int row = rt * 128 + w * 64 + wq * 16 + g;
      __nv_bfloat16* o0 = out + (size_t)row * D_ + dbase + 2 * t4;
#pragma unroll
      for (int j = 0; j < 7; j++) {
        uint4 v = lds128((j < 4) ? sA + j * 2048 : sB + (j - 4) * 2048);
        const float a0 = bf_round(keep[4 * j] + __uint_as_float(v.x)), a1 = bf_round(keep[4 * j + 1] + __uint_as_float(v.y));
        const float a2 = bf_round(keep[4 * j + 2] + __uint_as_float(v.z)), a3 = bf_round(keep[4 * j + 3] + __uint_as_float(v.w));
        *reinterpret_cast<uint32_t*>(o0 + 8 * j) = pack_bf16(bf_lo(hr[j][0]) + a0, bf_hi(hr[j][0]) + a1);
        *reinterpret_cast<uint32_t*>(o0 + 8 * D_ + 8 * j) = pack_bf16(bf_lo(hr[j][1]) + a2, bf_hi(hr[j][1]) + a3);
      }
    }
  }
}

typedef CUresult (*EncodeFn)(CUtensorMap*, CUtensorMapDataType, cuuint32_t, void*, const cuuint64_t*, const cuuint64_t*, const cuuint32_t*,
                             const cuuint32_t*, CUtensorMapInterleave, CUtensorMapSwizzle, CUtensorMapL2promotion, CUtensorMapFloatOOBfill);

static void make_map(EncodeFn enc, CUtensorMap* tm, const void* ptr, uint64_t inner, uint64_t outer, uint32_t box_in, uint32_t box_out,
                     CUtensorMapSwizzle swz) {
  cuuint64_t gd[2] = {inner, outer};
  cuuint64_t gs[1] = {inner * 2};
  cuuint32_t bd[2] = {box_in, box_out};
  cuuint32_t es[2] = {1, 1};
  enc(tm, CU_TENSOR_MAP_DATA_TYPE_BFLOAT16, 2, const_cast<void*>(ptr), gd, gs, bd, es, CU_TENSOR_MAP_INTERLEAVE_NONE, swz,
      CU_TENSOR_MAP_L2_PROMOTION_L2_256B, CU_TENSOR_MAP_FLOAT_OOB_FILL_NONE);
}

extern "C" void kernel_launch(void* const* d_in, const int* in_sizes, int n_in, void* d_out, int out_size) {
  (void)in_sizes; (void)n_in; (void)out_size;
  static EncodeFn enc = nullptr;
  static void* hT_ptr = nullptr;
  if (!enc) {
    void* fn = nullptr;
    cudaDriverEntryPointQueryResult qr;
    cudaGetDriverEntryPoint("cuTensorMapEncodeTiled", &fn, cudaEnableDefault, &qr);
    enc = (EncodeFn)fn;
    cudaGetSymbolAddress(&hT_ptr, g_hT);
    cudaFuncSetAttribute(s4_conv_kernel, cudaFuncAttributeMaxDynamicSharedMemorySize, A_SMEM);
    cudaFuncSetAttribute(glu_kernel, cudaFuncAttributeMaxDynamicSharedMemorySize, B_SMEM);
  }
  const __nv_bfloat16* const* in = reinterpret_cast<const __nv_bfloat16* const*>(d_in);
  AParams P;
  P.x = in[0];
  for (int i = 0; i < 6; i++) P.p[i] = in[1 + i];
  P.log_dt = in[7];
  P.dskip = in[8];
  P.wg = in[10];
  P.wu = in[11];
  P.wd = in[12];
  CUtensorMap tm_h, tm_wg, tm_wu, tm_wg32, tm_wu32, tm_wd;
  make_map(enc, &tm_h, hT_ptr, L_, D_, 64, 64, CU_TENSOR_MAP_SWIZZLE_128B);
  make_map(enc, &tm_wg, P.wg, F_, D_, 64, 32, CU_TENSOR_MAP_SWIZZLE_128B);
  make_map(enc, &tm_wu, P.wu, F_, D_, 64, 32, CU_TENSOR_MAP_SWIZZLE_128B);
  make_map(enc, &tm_wg32, P.wg, F_, D_, 32, 32, CU_TENSOR_MAP_SWIZZLE_64B);
  make_map(enc, &tm_wu32, P.wu, F_, D_, 32, 32, CU_TENSOR_MAP_SWIZZLE_64B);
  make_map(enc, &tm_wd, P.wd, D_, F_, 64, 32, CU_TENSOR_MAP_SWIZZLE_128B);

  cudaStream_t stream = cudaStreamPerThread;
  s4_conv_kernel<<<A_GRID, A_THREADS, A_SMEM, stream>>>(P);

  cudaLaunchConfig_t cfg = {};
  cfg.gridDim = dim3(128);
  cfg.blockDim = dim3(B_THREADS);
  cfg.dynamicSmemBytes = B_SMEM;
  cfg.stream = stream;
  cudaLaunchAttribute at[1];
  at[0].id = cudaLaunchAttributeProgrammaticStreamSerialization;
  at[0].val.programmaticStreamSerializationAllowed = 1;
  cfg.attrs = at;
  cfg.numAttrs = 1;
  cudaLaunchKernelEx(&cfg, glu_kernel, tm_h, tm_wg, tm_wu, tm_wg32, tm_wu32, tm_wd, (__nv_bfloat16*)d_out);
}
```

```cpp
#include <cuda_runtime.h>
#include <cuda_bf16.h>
#include <cuda.h>
#include <stdint.h>

constexpr int L_ = 2048, D_ = 448, NM_ = 256, F_ = 1792;

__device__ __align__(1024) __nv_bfloat16 g_hT[D_ * L_];
__device__ __align__(16) uint32_t g_stats[L_];
__device__ __align__(16) float g_csum[2 * F_];
__device__ __align__(16) uint4 g_H[16 * 8 * 8 * 14 * 32];
__device__ __align__(16) uint4 g_P[16 * 8 * 8 * 7 * 32];
__device__ __align__(16) uint2 g_st2[L_];
__device__ __align__(16) uint32_t g_epoch[4];

__device__ __forceinline__ uint32_t smem_u32(const void* p) { return (uint32_t)__cvta_generic_to_shared(p); }
__device__ __forceinline__ void mbar_init(uint32_t bar, int cnt) { asm volatile("mbarrier.init.shared::cta.b64 [%0], %1;" ::"r"(bar), "r"(cnt)); }
__device__ __forceinline__ void mbar_expect_tx(uint32_t bar, uint32_t bytes) {
  asm volatile("mbarrier.arrive.expect_tx.shared::cta.b64 _, [%0], %1;" ::"r"(bar), "r"(bytes) : "memory");
}
__device__ __forceinline__ void mbar_arrive(uint32_t bar) { asm volatile("mbarrier.arrive.shared::cta.b64 _, [%0];" ::"r"(bar) : "memory"); }
__device__ __forceinline__ void mbar_arrive_remote(uint32_t bar_cluster) {
  asm volatile("mbarrier.arrive.shared::cluster.b64 _, [%0];" ::"r"(bar_cluster) : "memory");
}
__device__ __forceinline__ void mbar_wait(uint32_t bar, uint32_t parity) {
  uint32_t ok;
  int it = 0;
  do {
    asm volatile("{\n.reg .pred p;\nmbarrier.try_wait.parity.shared::cta.b64 p, [%1], %2, %3;\nselp.u32 %0, 1, 0, p;\n}"
                 : "=r"(ok) : "r"(bar), "r"(parity), "r"(100000u) : "memory");
    if (++it > (1 << 14)) break;
  } while (!ok);
}
__device__ __forceinline__ void mbar_wait_cluster(uint32_t bar, uint32_t parity) {
  uint32_t ok;
  int it = 0;
  do {
    asm volatile("{\n.reg .pred p;\nmbarrier.try_wait.parity.acquire.cluster.shared::cta.b64 p, [%1], %2, %3;\nselp.u32 %0, 1, 0, p;\n}"
                 : "=r"(ok) : "r"(bar), "r"(parity), "r"(100000u) : "memory");
    if (++it > (1 << 14)) break;
  } while (!ok);
}
__device__ __forceinline__ bool elect_one() {
  uint32_t pred;
  asm volatile("{\n.reg .pred P;\nelect.sync _|P, 0xffffffff;\nselp.u32 %0, 1, 0, P;\n}" : "=r"(pred));
  return pred != 0;
}
__device__ __forceinline__ void tma_load_3d(uint32_t dst, const CUtensorMap* tm, int x, int y, int z, uint32_t bar) {
  asm volatile("cp.async.bulk.tensor.3d.shared::cluster.global.mbarrier::complete_tx::bytes [%0], [%1, {%3, %4, %5}], [%2];"
               ::"r"(dst), "l"((uint64_t)tm), "r"(bar), "r"(x), "r"(y), "r"(z) : "memory");
}
__device__ __forceinline__ void tma_load_3d_mc(uint32_t dst, const CUtensorMap* tm, int x, int y, int z, uint32_t bar) {
  asm volatile("cp.async.bulk.tensor.3d.shared::cluster.global.mbarrier::complete_tx::bytes.multicast::cluster [%0], [%1, {%3, %4, %5}], [%2], %6;"
               ::"r"(dst), "l"((uint64_t)tm), "r"(bar), "r"(x), "r"(y), "r"(z), "h"((uint16_t)3) : "memory");
}
__device__ __forceinline__ void tma_load_2d_mc(uint32_t dst, const CUtensorMap* tm, int x, int y, uint32_t bar) {
  asm volatile("cp.async.bulk.tensor.2d.shared::cluster.global.mbarrier::complete_tx::bytes.multicast::cluster [%0], [%1, {%3, %4}], [%2], %5;"
               ::"r"(dst), "l"((uint64_t)tm), "r"(bar), "r"(x), "r"(y), "h"((uint16_t)3) : "memory");
}
__device__ __forceinline__ void release_slot(uint32_t ebase, int slot, bool rel) {
  if (rel) mbar_arrive_remote(ebase + slot * 8);
}
__device__ __forceinline__ void bar_sync(int id, int n) { asm volatile("bar.sync %0, %1;" ::"r"(id), "r"(n) : "memory"); }
__device__ __forceinline__ void bar_arrive(int id, int n) { asm volatile("bar.arrive %0, %1;" ::"r"(id), "r"(n) : "memory"); }
__device__ __forceinline__ void fence_proxy_async() { asm volatile("fence.proxy.async.shared::cta;" ::: "memory"); }
#define WG_FENCE() asm volatile("wgmma.fence.sync.aligned;" ::: "memory")
#define WG_COMMIT() asm volatile("wgmma.commit_group.sync.aligned;" ::: "memory")
#define WG_WAIT(n) asm volatile("wgmma.wait_group.sync.aligned %0;" ::"n"(n) : "memory")
__device__ __forceinline__ uint64_t mkdesc(uint32_t addr, uint32_t lbo, uint32_t sbo, int swz) {
  return (uint64_t)((addr & 0x3FFFF) >> 4) | ((uint64_t)(lbo >> 4) << 16) | ((uint64_t)(sbo >> 4) << 32) | ((uint64_t)swz << 62);
}
__device__ __forceinline__ uint32_t pack_bf16(float lo, float hi) {
  uint32_t r;
  asm("cvt.rn.bf16x2.f32 %0, %1, %2;" : "=r"(r) : "f"(hi), "f"(lo));
  return r;
}
__device__ __forceinline__ float bf_lo(uint32_t v) { return __uint_as_float(v << 16); }
__device__ __forceinline__ float bf_hi(uint32_t v) { return __uint_as_float(v & 0xFFFF0000u); }
__device__ __forceinline__ uint32_t bf2_add(uint32_t a, uint32_t b) { uint32_t r; asm("add.rn.bf16x2 %0, %1, %2;" : "=r"(r) : "r"(a), "r"(b)); return r; }
__device__ __forceinline__ uint32_t bf2_mul(uint32_t a, uint32_t b) { uint32_t r; asm("mul.rn.bf16x2 %0, %1, %2;" : "=r"(r) : "r"(a), "r"(b)); return r; }
__device__ __forceinline__ float bf_round(float x) { return bf_lo(pack_bf16(x, 0.f)); }
__device__ __forceinline__ void tma_load_2d(uint32_t dst, const CUtensorMap* tm, int x, int y, uint32_t bar) {
  asm volatile("cp.async.bulk.tensor.2d.shared::cluster.global.mbarrier::complete_tx::bytes [%0], [%1, {%3, %4}], [%2];"
               ::"r"(dst), "l"((uint64_t)tm), "r"(bar), "r"(x), "r"(y) : "memory");
}
__device__ __forceinline__ void ldsm_x4_t(uint32_t& r0, uint32_t& r1, uint32_t& r2, uint32_t& r3, uint32_t addr) {
  asm volatile("ldmatrix.sync.aligned.m8n8.x4.trans.shared.b16 {%0,%1,%2,%3}, [%4];" : "=r"(r0), "=r"(r1), "=r"(r2), "=r"(r3) : "r"(addr) : "memory");
}
__device__ __forceinline__ void sts128(uint32_t addr, uint32_t a, uint32_t b, uint32_t c, uint32_t d) {
  asm volatile("st.shared.v4.b32 [%0], {%1,%2,%3,%4};" ::"r"(addr), "r"(a), "r"(b), "r"(c), "r"(d) : "memory");
}
__device__ __forceinline__ uint32_t lds32(uint32_t addr) {
  uint32_t r;
  asm volatile("ld.shared.b32 %0, [%1];" : "=r"(r) : "r"(addr) : "memory");
  return r;
}
__device__ __forceinline__ uint4 lds128(uint32_t addr) {
  uint4 r;
  asm volatile("ld.shared.v4.b32 {%0,%1,%2,%3}, [%4];" : "=r"(r.x), "=r"(r.y), "=r"(r.z), "=r"(r.w) : "r"(addr) : "memory");
  return r;
}
__device__ __forceinline__ uint2 lds64(uint32_t addr) {
  uint2 r;
  asm volatile("ld.shared.v2.b32 {%0,%1}, [%2];" : "=r"(r.x), "=r"(r.y) : "r"(addr) : "memory");
  return r;
}

template<int TA, int TB> __device__ __forceinline__ void wgmma_ss_f16_n48(float (&d)[24], uint64_t da, uint64_t db, int scale_d) {
  asm volatile("{\n.reg .pred p;\nsetp.ne.b32 p, %26, 0;\n"
    "wgmma.mma_async.sync.aligned.m64n48k16.f32.f16.f16 {%0, %1, %2, %3, %4, %5, %6, %7, %8, %9, %10, %11, %12, %13, %14, %15, %16, %17, %18, %19, %20, %21, %22, %23}, %24, %25, p, 1, 1, %27, %28;\n}"
    : "+f"(d[0]), "+f"(d[1]), "+f"(d[2]), "+f"(d[3]), "+f"(d[4]), "+f"(d[5]), "+f"(d[6]), "+f"(d[7]), "+f"(d[8]), "+f"(d[9]), "+f"(d[10]), "+f"(d[11]), "+f"(d[12]), "+f"(d[13]), "+f"(d[14]), "+f"(d[15]), "+f"(d[16]), "+f"(d[17]), "+f"(d[18]), "+f"(d[19]), "+f"(d[20]), "+f"(d[21]), "+f"(d[22]), "+f"(d[23])
    : "l"(da), "l"(db), "r"(scale_d), "n"(TA), "n"(TB));
}
template<int TA, int TB> __device__ __forceinline__ void wgmma_ss_n256(float (&d)[128], uint64_t da, uint64_t db, int scale_d) {
  asm volatile("{\n.reg .pred p;\nsetp.ne.b32 p, %130, 0;\n"
    "wgmma.mma_async.sync.aligned.m64n256k16.f32.bf16.bf16 {%0, %1, %2, %3, %4, %5, %6, %7, %8, %9, %10, %11, %12, %13, %14, %15, %16, %17, %18, %19, %20, %21, %22, %23, %24, %25, %26, %27, %28, %29, %30, %31, %32, %33, %34, %35, %36, %37, %38, %39, %40, %41, %42, %43, %44, %45, %46, %47, %48, %49, %50, %51, %52, %53, %54, %55, %56, %57, %58, %59, %60, %61, %62, %63, %64, %65, %66, %67, %68, %69, %70, %71, %72, %73, %74, %75, %76, %77, %78, %79, %80, %81, %82, %83, %84, %85, %86, %87, %88, %89, %90, %91, %92, %93, %94, %95, %96, %97, %98, %99, %100, %101, %102, %103, %104, %105, %106, %107, %108, %109, %110, %111, %112, %113, %114, %115, %116, %117, %118, %119, %120, %121, %122, %123, %124, %125, %126, %127}, %128, %129, p, 1, 1, %131, %132;\n}"
    : "+f"(d[0]), "+f"(d[1]), "+f"(d[2]), "+f"(d[3]), "+f"(d[4]), "+f"(d[5]), "+f"(d[6]), "+f"(d[7]), "+f"(d[8]), "+f"(d[9]), "+f"(d[10]), "+f"(d[11]), "+f"(d[12]), "+f"(d[13]), "+f"(d[14]), "+f"(d[15]), "+f"(d[16]), "+f"(d[17]), "+f"(d[18]), "+f"(d[19]), "+f"(d[20]), "+f"(d[21]), "+f"(d[22]), "+f"(d[23]), "+f"(d[24]), "+f"(d[25]), "+f"(d[26]), "+f"(d[27]), "+f"(d[28]), "+f"(d[29]), "+f"(d[30]), "+f"(d[31]), "+f"(d[32]), "+f"(d[33]), "+f"(d[34]), "+f"(d[35]), "+f"(d[36]), "+f"(d[37]), "+f"(d[38]), "+f"(d[39]), "+f"(d[40]), "+f"(d[41]), "+f"(d[42]), "+f"(d[43]), "+f"(d[44]), "+f"(d[45]), "+f"(d[46]), "+f"(d[47]), "+f"(d[48]), "+f"(d[49]), "+f"(d[50]), "+f"(d[51]), "+f"(d[52]), "+f"(d[53]), "+f"(d[54]), "+f"(d[55]), "+f"(d[56]), "+f"(d[57]), "+f"(d[58]), "+f"(d[59]), "+f"(d[60]), "+f"(d[61]), "+f"(d[62]), "+f"(d[63]), "+f"(d[64]), "+f"(d[65]), "+f"(d[66]), "+f"(d[67]), "+f"(d[68]), "+f"(d[69]), "+f"(d[70]), "+f"(d[71]), "+f"(d[72]), "+f"(d[73]), "+f"(d[74]), "+f"(d[75]), "+f"(d[76]), "+f"(d[77]), "+f"(d[78]), "+f"(d[79]), "+f"(d[80]), "+f"(d[81]), "+f"(d[82]), "+f"(d[83]), "+f"(d[84]), "+f"(d[85]), "+f"(d[86]), "+f"(d[87]), "+f"(d[88]), "+f"(d[89]), "+f"(d[90]), "+f"(d[91]), "+f"(d[92]), "+f"(d[93]), "+f"(d[94]), "+f"(d[95]), "+f"(d[96]), "+f"(d[97]), "+f"(d[98]), "+f"(d[99]), "+f"(d[100]), "+f"(d[101]), "+f"(d[102]), "+f"(d[103]), "+f"(d[104]), "+f"(d[105]), "+f"(d[106]), "+f"(d[107]), "+f"(d[108]), "+f"(d[109]), "+f"(d[110]), "+f"(d[111]), "+f"(d[112]), "+f"(d[113]), "+f"(d[114]), "+f"(d[115]), "+f"(d[116]), "+f"(d[117]), "+f"(d[118]), "+f"(d[119]), "+f"(d[120]), "+f"(d[121]), "+f"(d[122]), "+f"(d[123]), "+f"(d[124]), "+f"(d[125]), "+f"(d[126]), "+f"(d[127])
    : "l"(da), "l"(db), "r"(scale_d), "n"(TA), "n"(TB));
}
template<int TA, int TB> __device__ __forceinline__ void wgmma_ss_n192(float (&d)[96], uint64_t da, uint64_t db, int scale_d) {
  asm volatile("{\n.reg .pred p;\nsetp.ne.b32 p, %98, 0;\n"
    "wgmma.mma_async.sync.aligned.m64n192k16.f32.bf16.bf16 {%0, %1, %2, %3, %4, %5, %6, %7, %8, %9, %10, %11, %12, %13, %14, %15, %16, %17, %18, %19, %20, %21, %22, %23, %24, %25, %26, %27, %28, %29, %30, %31, %32, %33, %34, %35, %36, %37, %38, %39, %40, %41, %42, %43, %44, %45, %46, %47, %48, %49, %50, %51, %52, %53, %54, %55, %56, %57, %58, %59, %60, %61, %62, %63, %64, %65, %66, %67, %68, %69, %70, %71, %72, %73, %74, %75, %76, %77, %78, %79, %80, %81, %82, %83, %84, %85, %86, %87, %88, %89, %90, %91, %92, %93, %94, %95}, %96, %97, p, 1, 1, %99, %100;\n}"
    : "+f"(d[0]), "+f"(d[1]), "+f"(d[2]), "+f"(d[3]), "+f"(d[4]), "+f"(d[5]), "+f"(d[6]), "+f"(d[7]), "+f"(d[8]), "+f"(d[9]), "+f"(d[10]), "+f"(d[11]), "+f"(d[12]), "+f"(d[13]), "+f"(d[14]), "+f"(d[15]), "+f"(d[16]), "+f"(d[17]), "+f"(d[18]), "+f"(d[19]), "+f"(d[20]), "+f"(d[21]), "+f"(d[22]), "+f"(d[23]), "+f"(d[24]), "+f"(d[25]), "+f"(d[26]), "+f"(d[27]), "+f"(d[28]), "+f"(d[29]), "+f"(d[30]), "+f"(d[31]), "+f"(d[32]), "+f"(d[33]), "+f"(d[34]), "+f"(d[35]), "+f"(d[36]), "+f"(d[37]), "+f"(d[38]), "+f"(d[39]), "+f"(d[40]), "+f"(d[41]), "+f"(d[42]), "+f"(d[43]), "+f"(d[44]), "+f"(d[45]), "+f"(d[46]), "+f"(d[47]), "+f"(d[48]), "+f"(d[49]), "+f"(d[50]), "+f"(d[51]), "+f"(d[52]), "+f"(d[53]), "+f"(d[54]), "+f"(d[55]), "+f"(d[56]), "+f"(d[57]), "+f"(d[58]), "+f"(d[59]), "+f"(d[60]), "+f"(d[61]), "+f"(d[62]), "+f"(d[63]), "+f"(d[64]), "+f"(d[65]), "+f"(d[66]), "+f"(d[67]), "+f"(d[68]), "+f"(d[69]), "+f"(d[70]), "+f"(d[71]), "+f"(d[72]), "+f"(d[73]), "+f"(d[74]), "+f"(d[75]), "+f"(d[76]), "+f"(d[77]), "+f"(d[78]), "+f"(d[79]), "+f"(d[80]), "+f"(d[81]), "+f"(d[82]), "+f"(d[83]), "+f"(d[84]), "+f"(d[85]), "+f"(d[86]), "+f"(d[87]), "+f"(d[88]), "+f"(d[89]), "+f"(d[90]), "+f"(d[91]), "+f"(d[92]), "+f"(d[93]), "+f"(d[94]), "+f"(d[95])
    : "l"(da), "l"(db), "r"(scale_d), "n"(TA), "n"(TB));
}
template<int TB> __device__ __forceinline__ void wgmma_rs_n112(float (&d)[56], uint32_t a0, uint32_t a1, uint32_t a2, uint32_t a3, uint64_t db, int scale_d) {
  asm volatile("{\n.reg .pred p;\nsetp.ne.b32 p, %61, 0;\n"
    "wgmma.mma_async.sync.aligned.m64n112k16.f32.bf16.bf16 {%0, %1, %2, %3, %4, %5, %6, %7, %8, %9, %10, %11, %12, %13, %14, %15, %16, %17, %18, %19, %20, %21, %22, %23, %24, %25, %26, %27, %28, %29, %30, %31, %32, %33, %34, %35, %36, %37, %38, %39, %40, %41, %42, %43, %44, %45, %46, %47, %48, %49, %50, %51, %52, %53, %54, %55}, {%56, %57, %58, %59}, %60, p, 1, 1, %62;\n}"
    : "+f"(d[0]), "+f"(d[1]), "+f"(d[2]), "+f"(d[3]), "+f"(d[4]), "+f"(d[5]), "+f"(d[6]), "+f"(d[7]), "+f"(d[8]), "+f"(d[9]), "+f"(d[10]), "+f"(d[11]), "+f"(d[12]), "+f"(d[13]), "+f"(d[14]), "+f"(d[15]), "+f"(d[16]), "+f"(d[17]), "+f"(d[18]), "+f"(d[19]), "+f"(d[20]), "+f"(d[21]), "+f"(d[22]), "+f"(d[23]), "+f"(d[24]), "+f"(d[25]), "+f"(d[26]), "+f"(d[27]), "+f"(d[28]), "+f"(d[29]), "+f"(d[30]), "+f"(d[31]), "+f"(d[32]), "+f"(d[33]), "+f"(d[34]), "+f"(d[35]), "+f"(d[36]), "+f"(d[37]), "+f"(d[38]), "+f"(d[39]), "+f"(d[40]), "+f"(d[41]), "+f"(d[42]), "+f"(d[43]), "+f"(d[44]), "+f"(d[45]), "+f"(d[46]), "+f"(d[47]), "+f"(d[48]), "+f"(d[49]), "+f"(d[50]), "+f"(d[51]), "+f"(d[52]), "+f"(d[53]), "+f"(d[54]), "+f"(d[55])
    : "r"(a0), "r"(a1), "r"(a2), "r"(a3), "l"(db), "r"(scale_d), "n"(TB));
}
template<int TB> __device__ __forceinline__ void wgmma_rs_n32(float (&d)[16], uint32_t a0, uint32_t a1, uint32_t a2, uint32_t a3, uint64_t db, int scale_d) {
  asm volatile("{\n.reg .pred p;\nsetp.ne.b32 p, %21, 0;\n"
    "wgmma.mma_async.sync.aligned.m64n32k16.f32.bf16.bf16 {%0, %1, %2, %3, %4, %5, %6, %7, %8, %9, %10, %11, %12, %13, %14, %15}, {%16, %17, %18, %19}, %20, p, 1, 1, %22;\n}"
    : "+f"(d[0]), "+f"(d[1]), "+f"(d[2]), "+f"(d[3]), "+f"(d[4]), "+f"(d[5]), "+f"(d[6]), "+f"(d[7]), "+f"(d[8]), "+f"(d[9]), "+f"(d[10]), "+f"(d[11]), "+f"(d[12]), "+f"(d[13]), "+f"(d[14]), "+f"(d[15])
    : "r"(a0), "r"(a1), "r"(a2), "r"(a3), "l"(db), "r"(scale_d), "n"(TB));
}
template<int TB> __device__ __forceinline__ void wgmma_rs_n64(float (&d)[32], uint32_t a0, uint32_t a1, uint32_t a2, uint32_t a3, uint64_t db, int scale_d) {
  asm volatile("{\n.reg .pred p;\nsetp.ne.b32 p, %37, 0;\n"
    "wgmma.mma_async.sync.aligned.m64n64k16.f32.bf16.bf16 {%0, %1, %2, %3, %4, %5, %6, %7, %8, %9, %10, %11, %12, %13, %14, %15, %16, %17, %18, %19, %20, %21, %22, %23, %24, %25, %26, %27, %28, %29, %30, %31}, {%32, %33, %34, %35}, %36, p, 1, 1, %38;\n}"
    : "+f"(d[0]), "+f"(d[1]), "+f"(d[2]), "+f"(d[3]), "+f"(d[4]), "+f"(d[5]), "+f"(d[6]), "+f"(d[7]), "+f"(d[8]), "+f"(d[9]), "+f"(d[10]), "+f"(d[11]), "+f"(d[12]), "+f"(d[13]), "+f"(d[14]), "+f"(d[15]), "+f"(d[16]), "+f"(d[17]), "+f"(d[18]), "+f"(d[19]), "+f"(d[20]), "+f"(d[21]), "+f"(d[22]), "+f"(d[23]), "+f"(d[24]), "+f"(d[25]), "+f"(d[26]), "+f"(d[27]), "+f"(d[28]), "+f"(d[29]), "+f"(d[30]), "+f"(d[31])
    : "r"(a0), "r"(a1), "r"(a2), "r"(a3), "l"(db), "r"(scale_d), "n"(TB));
}
template<int TB> __device__ __forceinline__ void wgmma_rs_n128(float (&d)[64], uint32_t a0, uint32_t a1, uint32_t a2, uint32_t a3, uint64_t db, int scale_d) {
  asm volatile("{\n.reg .pred p;\nsetp.ne.b32 p, %69, 0;\n"
    "wgmma.mma_async.sync.aligned.m64n128k16.f32.bf16.bf16 {%0, %1, %2, %3, %4, %5, %6, %7, %8, %9, %10, %11, %12, %13, %14, %15, %16, %17, %18, %19, %20, %21, %22, %23, %24, %25, %26, %27, %28, %29, %30, %31, %32, %33, %34, %35, %36, %37, %38, %39, %40, %41, %42, %43, %44, %45, %46, %47, %48, %49, %50, %51, %52, %53, %54, %55, %56, %57, %58, %59, %60, %61, %62, %63}, {%64, %65, %66, %67}, %68, p, 1, 1, %70;\n}"
    : "+f"(d[0]), "+f"(d[1]), "+f"(d[2]), "+f"(d[3]), "+f"(d[4]), "+f"(d[5]), "+f"(d[6]), "+f"(d[7]), "+f"(d[8]), "+f"(d[9]), "+f"(d[10]), "+f"(d[11]), "+f"(d[12]), "+f"(d[13]), "+f"(d[14]), "+f"(d[15]), "+f"(d[16]), "+f"(d[17]), "+f"(d[18]), "+f"(d[19]), "+f"(d[20]), "+f"(d[21]), "+f"(d[22]), "+f"(d[23]), "+f"(d[24]), "+f"(d[25]), "+f"(d[26]), "+f"(d[27]), "+f"(d[28]), "+f"(d[29]), "+f"(d[30]), "+f"(d[31]), "+f"(d[32]), "+f"(d[33]), "+f"(d[34]), "+f"(d[35]), "+f"(d[36]), "+f"(d[37]), "+f"(d[38]), "+f"(d[39]), "+f"(d[40]), "+f"(d[41]), "+f"(d[42]), "+f"(d[43]), "+f"(d[44]), "+f"(d[45]), "+f"(d[46]), "+f"(d[47]), "+f"(d[48]), "+f"(d[49]), "+f"(d[50]), "+f"(d[51]), "+f"(d[52]), "+f"(d[53]), "+f"(d[54]), "+f"(d[55]), "+f"(d[56]), "+f"(d[57]), "+f"(d[58]), "+f"(d[59]), "+f"(d[60]), "+f"(d[61]), "+f"(d[62]), "+f"(d[63])
    : "r"(a0), "r"(a1), "r"(a2), "r"(a3), "l"(db), "r"(scale_d), "n"(TB));
}


constexpr int A_THREADS = 512;
constexpr int A_CONV_CTAS = 112;
constexpr int A_GRID = 132;
constexpr int EPI_PITCH = 136;
constexpr int EPI_WARP = 16 * EPI_PITCH * 4;
constexpr int KC_PITCH = 36;
constexpr int KC_HALF = 24 * KC_PITCH * 4;
constexpr int KREV_COPY = 4160;
constexpr int WG_KREV = 8192;
constexpr int A_WGREG = 4 * EPI_WARP;
static_assert(A_WGREG % 1024 == 0 && A_WGREG >= 32768, "region");
constexpr int UPL_PAD = 960;
constexpr int UPL_PLANE = 2048 + UPL_PAD;
constexpr int A_UPL = 4 * A_WGREG;
constexpr int A_XS = A_UPL + 8 * UPL_PLANE;
constexpr int A_XST = A_XS + 16384;
constexpr int A_BAR = A_XST + 32768;
constexpr int A_SMEM = A_BAR + 16 + 64;

__device__ const __align__(16) uint16_t c_kidx[2064] = {
  2880,2880,2880,2880,2880,2860,2860,2860,2860,2860,2860,2860,2856,2856,2856,2856,2856,2856,2856,2856,2856,2852,2852,2852,
  2852,2852,2852,2852,2848,2848,2848,2848,2848,2848,2848,2848,2848,2844,2844,2844,2844,2844,2844,2844,2840,2840,2840,2840,
  2840,2840,2840,2840,2840,2836,2836,2836,2836,2836,2836,2836,2832,2832,2832,2832,2832,2832,2832,2832,2832,2828,2828,2828,
  2828,2828,2828,2828,2824,2824,2824,2824,2824,2824,2824,2824,2824,2820,2820,2820,2820,2820,2820,2820,2816,2816,2816,2816,
  2816,2816,2816,2816,2816,2812,2812,2812,2812,2812,2812,2812,2808,2808,2808,2808,2808,2808,2808,2808,2808,2804,2804,2804,
  2804,2804,2804,2804,2800,2800,2800,2800,2800,2800,2800,2800,2800,2796,2796,2796,2796,2796,2796,2796,2792,2792,2792,2792,
  2792,2792,2792,2792,2792,2788,2788,2788,2788,2788,2788,2788,2784,2784,2784,2784,2784,2784,2784,2784,2784,2780,2780,2780,
  2780,2780,2780,2780,2776,2776,2776,2776,2776,2776,2776,2776,2776,2772,2772,2772,2772,2772,2772,2772,2768,2768,2768,2768,
  2768,2768,2768,2768,2768,2764,2764,2764,2764,2764,2764,2764,2760,2760,2760,2760,2760,2760,2760,2760,2760,2756,2756,2756,
  2756,2756,2756,2756,2752,2752,2752,2752,2752,2752,2752,2752,2752,2748,2748,2748,2748,2748,2748,2748,2744,2744,2744,2744,
  2744,2744,2744,2744,2744,2740,2740,2740,2740,2740,2740,2740,2736,2736,2736,2736,2736,2736,2736,2736,2736,2716,2716,2716,
  2716,2716,2716,2716,2712,2712,2712,2712,2712,2712,2712,2712,2712,2708,2708,2708,2708,2708,2708,2708,2704,2704,2704,2704,
  2704,2704,2704,2704,2704,2700,2700,2700,2700,2700,2700,2700,2696,2696,2696,2696,2696,2696,2696,2696,2696,2692,2692,2692,
  2692,2692,2692,2692,2688,2688,2688,2688,2688,2688,2688,2688,2688,2684,2684,2684,2684,2684,2684,2684,2680,2680,2680,2680,
  2680,2680,2680,2680,2680,2676,2676,2676,2676,2676,2676,2676,2672,2672,2672,2672,2672,2672,2672,2672,2672,2668,2668,2668,
  2668,2668,2668,2668,2664,2664,2664,2664,2664,2664,2664,2664,2664,2660,2660,2660,2660,2660,2660,2660,2656,2656,2656,2656,
  2656,2656,2656,2656,2656,2652,2652,2652,2652,2652,2652,2652,2648,2648,2648,2648,2648,2648,2648,2648,2648,2644,2644,2644,
  2644,2644,2644,2644,2640,2640,2640,2640,2640,2640,2640,2640,2640,2636,2636,2636,2636,2636,2636,2636,2632,2632,2632,2632,
  2632,2632,2632,2632,2632,2628,2628,2628,2628,2628,2628,2628,2624,2624,2624,2624,2624,2624,2624,2624,2624,2620,2620,2620,
  2620,2620,2620,2620,2616,2616,2616,2616,2616,2616,2616,2616,2616,2612,2612,2612,2612,2612,2612,2612,2608,2608,2608,2608,
  2608,2608,2608,2608,2608,2604,2604,2604,2604,2604,2604,2604,2600,2600,2600,2600,2600,2600,2600,2600,2600,2596,2596,2596,
  2596,2596,2596,2596,2592,2592,2592,2592,2592,2592,2592,2592,2592,2572,2572,2572,2572,2572,2572,2572,2568,2568,2568,2568,
  2568,2568,2568,2568,2568,2564,2564,2564,2564,2564,2564,2564,2560,2560,2560,2560,2560,2560,2560,2560,2560,2556,2556,2556,
  2556,2556,2556,2556,2552,2552,2552,2552,2552,2552,2552,2552,2552,2548,2548,2548,2548,2548,2548,2548,2544,2544,2544,2544,
  2544,2544,2544,2544,2544,2540,2540,2540,2540,2540,2540,2540,2536,2536,2536,2536,2536,2536,2536,2536,2536,2532,2532,2532,
  2532,2532,2532,2532,2528,2528,2528,2528,2528,2528,2528,2528,2528,2524,2524,2524,2524,2524,2524,2524,2520,2520,2520,2520,
  2520,2520,2520,2520,2520,2516,2516,2516,2516,2516,2516,2516,2512,2512,2512,2512,2512,2512,2512,2512,2512,2508,2508,2508,
  2508,2508,2508,2508,2504,2504,2504,2504,2504,2504,2504,2504,2504,2500,2500,2500,2500,2500,2500,2500,2496,2496,2496,2496,
  2496,2496,2496,2496,2496,2492,2492,2492,2492,2492,2492,2492,2488,2488,2488,2488,2488,2488,2488,2488,2488,2484,2484,2484,
  2484,2484,2484,2484,2480,2480,2480,2480,2480,2480,2480,2480,2480,2476,2476,2476,2476,2476,2476,2476,2472,2472,2472,2472,
  2472,2472,2472,2472,2472,2468,2468,2468,2468,2468,2468,2468,2464,2464,2464,2464,2464,2464,2464,2464,2464,2460,2460,2460,
  2460,2460,2460,2460,2456,2456,2456,2456,2456,2456,2456,2456,2456,2452,2452,2452,2452,2452,2452,2452,2448,2448,2448,2448,
  2448,2448,2448,2448,2448,2428,2428,2428,2428,2428,2428,2428,2424,2424,2424,2424,2424,2424,2424,2424,2424,2420,2420,2420,
  2420,2420,2420,2420,2416,2416,2416,2416,2416,2416,2416,2416,2416,2412,2412,2412,2412,2412,2412,2412,2408,2408,2408,2408,
  2408,2408,2408,2408,2408,2404,2404,2404,2404,2404,2404,2404,2400,2400,2400,2400,2400,2400,2400,2400,2400,2396,2396,2396,
  2396,2396,2396,2396,2392,2392,2392,2392,2392,2392,2392,2392,2392,2388,2388,2388,2388,2388,2388,2388,2384,2384,2384,2384,
  2384,2384,2384,2384,2384,2380,2380,2380,2380,2380,2380,2380,2376,2376,2376,2376,2376,2376,2376,2376,2376,2372,2372,2372,
  2372,2372,2372,2372,2368,2368,2368,2368,2368,2368,2368,2368,2368,2364,2364,2364,2364,2364,2364,2364,2360,2360,2360,2360,
  2360,2360,2360,2360,2360,2356,2356,2356,2356,2356,2356,2356,2352,2352,2352,2352,2352,2352,2352,2352,2352,2348,2348,2348,
  2348,2348,2348,2348,2344,2344,2344,2344,2344,2344,2344,2344,2344,2340,2340,2340,2340,2340,2340,2340,2336,2336,2336,2336,
  2336,2336,2336,2336,2336,2332,2332,2332,2332,2332,2332,2332,2328,2328,2328,2328,2328,2328,2328,2328,2328,2324,2324,2324,
  2324,2324,2324,2324,2320,2320,2320,2320,2320,2320,2320,2320,2320,2316,2316,2316,2316,2316,2316,2316,2312,2312,2312,2312,
  2312,2312,2312,2312,2312,2308,2308,2308,2308,2308,2308,2308,2304,2304,2304,2304,2304,2304,2304,2284,2284,2284,2140,2140,
  2140,2140,2140,2280,2280,2280,2136,2136,2136,2136,2136,2276,2276,2276,2132,2132,2132,2132,2132,2272,2272,2272,2128,2128,
  2128,2128,2128,2268,2268,2268,2124,2124,2124,2124,2124,2264,2264,2264,2120,2120,2120,2120,2120,2260,2260,2260,2116,2116,
  2116,2116,2116,2256,2256,2256,2112,2112,2112,2112,2112,2252,2252,2252,2108,2108,2108,2108,2108,2248,2248,2248,2104,2104,
  2104,2104,2104,2244,2244,2244,2100,2100,2100,2100,2100,2240,2240,2240,2096,2096,2096,2096,2096,2236,2236,2236,2092,2092,
  2092,2092,2092,2232,2232,2232,2088,2088,2088,2088,2088,2228,2228,2228,2084,2084,2084,2084,2084,2224,2224,2224,2080,2080,
  2080,2080,2080,2220,2220,2220,2076,2076,2076,2076,2076,2216,2216,2216,2072,2072,2072,2072,2072,2212,2212,2212,2068,2068,
  2068,2068,2068,2208,2208,2208,2064,2064,2064,2064,2064,2204,2204,2204,2060,2060,2060,2060,2060,2200,2200,2200,2056,2056,
  2056,2056,2056,2196,2196,2196,2052,2052,2052,2052,2052,2192,2192,2192,2048,2048,2048,2048,2048,2188,2188,2188,2044,2044,
  2044,2044,2044,2184,2184,2184,2040,2040,2040,2040,2040,2180,2180,2180,2036,2036,2036,2036,2036,2176,2176,2176,2032,2032,
  2032,2032,2032,2172,2172,2172,2028,2028,2028,2028,2028,2168,2168,2168,2024,2024,2024,2024,2024,2164,2164,2164,2020,2020,
  2020,2020,2020,2160,2160,2160,2016,2016,2016,2016,2016,1996,1996,1996,1852,1852,1852,1852,1852,1992,1992,1992,1848,1848,
  1848,1848,1848,1988,1988,1988,1844,1844,1844,1844,1844,1984,1984,1984,1840,1840,1840,1840,1840,1980,1980,1980,1836,1836,
  1836,1836,1836,1976,1976,1976,1832,1832,1832,1832,1832,1972,1972,1972,1828,1828,1828,1828,1828,1968,1968,1968,1824,1824,
  1824,1824,1824,1964,1964,1964,1820,1820,1820,1820,1820,1960,1960,1960,1816,1816,1816,1816,1816,1956,1956,1956,1812,1812,
  1812,1812,1812,1952,1952,1952,1808,1808,1808,1808,1808,1948,1948,1948,1804,1804,1804,1804,1804,1944,1944,1944,1800,1800,
  1800,1800,1800,1940,1940,1940,1796,1796,1796,1796,1796,1936,1936,1936,1792,1792,1792,1792,1792,1932,1932,1932,1788,1788,
  1788,1788,1788,1928,1928,1928,1784,1784,1784,1784,1784,1924,1924,1924,1780,1780,1780,1780,1780,1920,1920,1920,1776,1776,
  1776,1776,1776,1916,1916,1916,1772,1772,1772,1772,1772,1912,1912,1912,1768,1768,1768,1768,1768,1908,1908,1908,1764,1764,
  1764,1764,1764,1904,1904,1904,1760,1760,1760,1760,1760,1900,1900,1900,1756,1756,1756,1756,1756,1896,1896,1896,1752,1752,
  1752,1752,1752,1892,1892,1892,1748,1748,1748,1748,1748,1888,1888,1888,1744,1744,1744,1744,1744,1884,1884,1884,1740,1740,
  1740,1740,1740,1880,1880,1880,1736,1736,1736,1736,1736,1876,1876,1876,1732,1732,1732,1732,1732,1872,1872,1872,1728,1728,
  1728,1728,1708,1564,1564,1564,1420,1276,1276,1276,1704,1560,1560,1560,1416,1272,1272,1272,1700,1556,1556,1556,1412,1268,
  1268,1268,1696,1552,1552,1552,1408,1264,1264,1264,1692,1548,1548,1548,1404,1260,1260,1260,1688,1544,1544,1544,1400,1256,
  1256,1256,1684,1540,1540,1540,1396,1252,1252,1252,1680,1536,1536,1536,1392,1248,1248,1248,1676,1532,1532,1532,1388,1244,
  1244,1244,1672,1528,1528,1528,1384,1240,1240,1240,1668,1524,1524,1524,1380,1236,1236,1236,1664,1520,1520,1520,1376,1232,
  1232,1232,1660,1516,1516,1516,1372,1228,1228,1228,1656,1512,1512,1512,1368,1224,1224,1224,1652,1508,1508,1508,1364,1220,
  1220,1220,1648,1504,1504,1504,1360,1216,1216,1216,1644,1500,1500,1500,1356,1212,1212,1212,1640,1496,1496,1496,1352,1208,
  1208,1208,1636,1492,1492,1492,1348,1204,1204,1204,1632,1488,1488,1488,1344,1200,1200,1200,1628,1484,1484,1484,1340,1196,
  1196,1196,1624,1480,1480,1480,1336,1192,1192,1192,1620,1476,1476,1476,1332,1188,1188,1188,1616,1472,1472,1472,1328,1184,
  1184,1184,1612,1468,1468,1468,1324,1180,1180,1180,1608,1464,1464,1464,1320,1176,1176,1176,1604,1460,1460,1460,1316,1172,
  1172,1172,1600,1456,1456,1456,1312,1168,1168,1168,1596,1452,1452,1452,1308,1164,1164,1164,1592,1448,1448,1448,1304,1160,
  1160,1160,1588,1444,1444,1444,1300,1156,1156,1156,1584,1440,1440,1440,1296,1152,1152,1132,988,844,700,556,412,268,
  124,1128,984,840,696,552,408,264,120,1124,980,836,692,548,404,260,116,1120,976,832,688,544,400,256,
  112,1116,972,828,684,540,396,252,108,1112,968,824,680,536,392,248,104,1108,964,820,676,532,388,244,
  100,1104,960,816,672,528,384,240,96,1100,956,812,668,524,380,236,92,1096,952,808,664,520,376,232,
  88,1092,948,804,660,516,372,228,84,1088,944,800,656,512,368,224,80,1084,940,796,652,508,364,220,
  76,1080,936,792,648,504,360,216,72,1076,932,788,644,500,356,212,68,1072,928,784,640,496,352,208,
  64,1068,924,780,636,492,348,204,60,1064,920,776,632,488,344,200,56,1060,916,772,628,484,340,196,
  52,1056,912,768,624,480,336,192,48,1052,908,764,620,476,332,188,44,1048,904,760,616,472,328,184,
  40,1044,900,756,612,468,324,180,36,1040,896,752,608,464,320,176,32,1036,892,748,604,460,316,172,
  28,1032,888,744,600,456,312,168,24,1028,884,740,596,452,308,164,20,1024,880,736,592,448,304,160,
  16,1020,876,732,588,444,300,156,12,1016,872,728,584,440,296,152,8,1012,868,724,580,436,292,148,
  4,1008,864,720,576,432,288,144,0,0,0,0,0,0,0,0,0,0,0,0,0,0,0,0,
};

struct cplx { float r, i; };
__device__ __forceinline__ cplx cmul(cplx a, cplx b) {
  cplx c;
  c.r = fmaf(a.r, b.r, -a.i * b.i);
  c.i = fmaf(a.r, b.i, a.i * b.r);
  return c;
}
__device__ __forceinline__ cplx cexp_t(float lr2, float rv, float t) {
  float mag;
  asm("ex2.approx.ftz.f32 %0, %1;" : "=f"(mag) : "f"(lr2 * t));
  float ph = rv * t;
  ph = (ph - rintf(ph)) * 6.283185307179586f;
  cplx c;
  c.r = mag * __cosf(ph);
  c.i = mag * __sinf(ph);
  return c;
}
__device__ __forceinline__ uint32_t pack_f16(float lo, float hi) {
  uint32_t r;
  asm("cvt.rn.f16x2.f32 %0, %1, %2;" : "=r"(r) : "f"(hi), "f"(lo));
  return r;
}
__device__ __forceinline__ uint32_t h2mul(uint32_t a, uint32_t b) { uint32_t r; asm("mul.rn.f16x2 %0, %1, %2;" : "=r"(r) : "r"(a), "r"(b)); return r; }
__device__ __forceinline__ uint32_t h2fma(uint32_t a, uint32_t b, uint32_t c) { uint32_t r; asm("fma.rn.f16x2 %0, %1, %2, %3;" : "=r"(r) : "r"(a), "r"(b), "r"(c)); return r; }
struct Anchors { cplx e1, e2, e4, e8, e16, e32, e64, e256; };
__device__ __forceinline__ Anchors kgen_anchors(float lr, float li) {
  const float lr2 = lr * 1.4426950408889634f, rv = li * 0.15915494309189535f;
  Anchors a;
  a.e1 = cexp_t(lr2, rv, 1.f);
  a.e256 = cexp_t(lr2, rv, 256.f);
  a.e2 = cmul(a.e1, a.e1); a.e4 = cmul(a.e2, a.e2); a.e8 = cmul(a.e4, a.e4);
  a.e16 = cmul(a.e8, a.e8); a.e32 = cmul(a.e16, a.e16); a.e64 = cmul(a.e32, a.e32);
  return a;
}
__device__ __forceinline__ cplx csel(bool p, cplx a, cplx b) { cplx c; c.r = p ? a.r : b.r; c.i = p ? a.i : b.i; return c; }
__device__ __forceinline__ void kgen_tables(const Anchors& A0, const Anchors& A1, bool second, cplx w, uint32_t tbl, int tid128, int bar_id) {
  const cplx e1 = csel(second, A1.e1, A0.e1), e2 = csel(second, A1.e2, A0.e2), e4 = csel(second, A1.e4, A0.e4), e8 = csel(second, A1.e8, A0.e8);
  const cplx z2 = csel(second, A1.e16, A0.e16), z4 = csel(second, A1.e32, A0.e32), e64 = csel(second, A1.e64, A0.e64), e256 = csel(second, A1.e256, A0.e256);
  const bool wait_prev = second;
  const uint32_t erow = tbl + tid128 * 128 + ((tid128 & 7) << 4), xrow = erow + 16384;
  uint32_t xp[22];
  {
    cplx c1 = e1, c256 = e256;
    c1.i = -c1.i; c256.i = -c256.i;
    cplx x[8];
    x[0].r = w.r; x[0].i = -w.i;
    cplx c2 = e2, c4 = e4;
    c2.i = -c2.i; c4.i = -c4.i;
    x[1] = cmul(x[0], c1);
    x[2] = cmul(x[0], c2);
    x[3] = cmul(x[1], c2);
#pragma unroll
    for (int j = 0; j < 4; j++) x[4 + j] = cmul(x[j], c4);
    cplx y[8];
    y[0] = cmul(x[0], c256); y[1] = cmul(x[2], c256); y[2] = cmul(x[4], c256); y[3] = cmul(x[6], c256);
    y[4] = cmul(y[0], c256); y[5] = cmul(y[2], c256); y[6] = cmul(y[4], c256); y[7] = cmul(y[5], c256);
    const cplx c512 = cmul(c256, c256);
    const cplx w0 = cmul(y[4], c512);
    const cplx w1 = cmul(y[6], c512);
    const cplx w2 = cmul(w0, c512);
    const cplx w3 = cmul(w1, c512);
    const cplx w4 = cmul(w2, c512);
#pragma unroll
    for (int j = 0; j < 4; j++) {
      xp[j] = pack_f16(x[2 * j].r, x[2 * j + 1].r); xp[4 + j] = pack_f16(x[2 * j].i, x[2 * j + 1].i);
      xp[8 + j] = pack_f16(y[2 * j].r, y[2 * j + 1].r); xp[12 + j] = pack_f16(y[2 * j].i, y[2 * j + 1].i);
    }
    xp[16] = pack_f16(w0.r, w1.r); xp[17] = pack_f16(w2.r, w3.r); xp[18] = pack_f16(w4.r, 0.f);
    xp[19] = pack_f16(w0.i, w1.i); xp[20] = pack_f16(w2.i, w3.i); xp[21] = pack_f16(w4.i, 0.f);
  }
  const cplx z3 = cmul(z2, e8), z5 = cmul(z4, e8), z6 = cmul(z4, z2), z7 = cmul(z4, z3);
  uint32_t zr[4] = {pack_f16(1.f, e8.r), pack_f16(z2.r, z3.r), pack_f16(z4.r, z5.r), pack_f16(z6.r, z7.r)};
  uint32_t zi[4] = {pack_f16(0.f, e8.i), pack_f16(z2.i, z3.i), pack_f16(z4.i, z5.i), pack_f16(z6.i, z7.i)};
  const cplx e128 = cmul(e64, e64), e192 = cmul(e128, e64);
  uint32_t ar[3] = {pack_f16(e64.r, e64.r), pack_f16(e128.r, e128.r), pack_f16(e192.r, e192.r)};
  uint32_t ai[3] = {pack_f16(e64.i, e64.i), pack_f16(e128.i, e128.i), pack_f16(e192.i, e192.i)};
#pragma unroll
  for (int j = 0; j < 22; j++) asm volatile("" : "+r"(xp[j]));
#pragma unroll
  for (int j = 0; j < 4; j++) asm volatile("" : "+r"(zr[j]), "+r"(zi[j]));
#pragma unroll
  for (int j = 0; j < 3; j++) asm volatile("" : "+r"(ar[j]), "+r"(ai[j]));
  if (wait_prev) {
    WG_WAIT(0);
    bar_sync(bar_id, 128);
  }
  sts128(xrow, xp[0], xp[1], xp[2], xp[3]);
  sts128(xrow ^ 48u, xp[4], xp[5], xp[6], xp[7]);
  sts128(xrow ^ 16u, xp[8], xp[9], xp[10], xp[11]);
  sts128(xrow ^ 64u, xp[12], xp[13], xp[14], xp[15]);
  sts128(xrow ^ 32u, xp[16], xp[17], xp[18], 0u);
  sts128(xrow ^ 80u, xp[19], xp[20], xp[21], 0u);
  sts128(erow, zr[0], zr[1], zr[2], zr[3]);
  sts128(erow ^ 64u, zi[0], zi[1], zi[2], zi[3]);
#pragma unroll
  for (int g = 1; g < 4; g++) {
    const uint32_t nai = ai[g - 1] ^ 0x80008000u;
    uint32_t nr[4], ni[4];
#pragma unroll
    for (int j = 0; j < 4; j++) {
      nr[j] = h2fma(zr[j], ar[g - 1], h2mul(zi[j], nai));
      ni[j] = h2fma(zr[j], ai[g - 1], h2mul(zi[j], ar[g - 1]));
    }
    sts128(erow ^ (uint32_t)(g * 16), nr[0], nr[1], nr[2], nr[3]);
    sts128(erow ^ (uint32_t)(64 + g * 16), ni[0], ni[1], ni[2], ni[3]);
  }
  fence_proxy_async();
  bar_sync(bar_id, 128);
}

template <int S0>
__device__ __forceinline__ void conv_frags4(uint32_t (&a)[4][4], uint32_t kaddr) {
#pragma unroll
  for (int s = 0; s < 4; s++) {
    const uint32_t ad = kaddr - (uint32_t)((S0 + s) * 128);
    a[s][0] = lds32(ad); a[s][1] = lds32(ad - 16); a[s][2] = lds32(ad + 16); a[s][3] = a[s][0];
  }
}

__device__ __forceinline__ uint32_t row_stats(const uint32_t (&v)[7]) {
  float s = 0.f;
#pragma unroll
  for (int j = 0; j < 7; j++) s += bf_lo(v[j]) + bf_hi(v[j]);
#pragma unroll
  for (int o = 16; o; o >>= 1) s += __shfl_xor_sync(0xffffffffu, s, o);
  const float mean = s * (1.f / D_);
  float q = 0.f;
#pragma unroll
  for (int j = 0; j < 7; j++) {
    float a = bf_lo(v[j]) - mean, b = bf_hi(v[j]) - mean;
    q = fmaf(a, a, q);
    q = fmaf(b, b, q);
  }
#pragma unroll
  for (int o = 16; o; o >>= 1) q += __shfl_xor_sync(0xffffffffu, q, o);
  const float var = bf_round(q * (1.f / D_));
  float den;
  asm("sqrt.approx.f32 %0, %1;" : "=f"(den) : "f"(bf_round(var + 1e-5f)));
  return pack_bf16(mean, den);
}

struct AParams {
  const __nv_bfloat16* x;
  const __nv_bfloat16* p[6];
  const __nv_bfloat16* log_dt;
  const __nv_bfloat16* dskip;
  const __nv_bfloat16* wg;
  const __nv_bfloat16* wu;
  const __nv_bfloat16* wd;
};

__global__ void __launch_bounds__(A_THREADS, 1) s4_conv_kernel(const AParams P, const __grid_constant__ CUtensorMap tm_x) {
  extern __shared__ __align__(1024) unsigned char smem[];
  const int tid = threadIdx.x, warp = __shfl_sync(0xffffffffu, tid >> 5, 0), lane = tid & 31, wg = warp >> 2, tid128 = tid & 127;
  const uint32_t sbase = smem_u32(smem);
  asm volatile("griddepcontrol.launch_dependents;");
  const bool is_conv = blockIdx.x < A_CONV_CTAS;
  const int d = blockIdx.x * 4 + wg;
  uint32_t xr[7];
  if (blockIdx.x < 128) {
    const uint32_t* xrow = reinterpret_cast<const uint32_t*>(P.x + (size_t)(blockIdx.x * 16 + warp) * D_);
#pragma unroll
    for (int j = 0; j < 7; j++) xr[j] = __ldg(xrow + lane + 32 * j);
  }
  uint32_t pm[6];
  float ldt = 0.f, dskip = 0.f;
  if (is_conv) {
#pragma unroll
    for (int j = 0; j < 6; j++) pm[j] = __ldg(reinterpret_cast<const uint32_t*>(P.p[j] + d * NM_) + tid128);
    ldt = __bfloat162float(P.log_dt[d]);
    dskip = __bfloat162float(P.dskip[d]);
  }
  if (blockIdx.x < 128) {
    const uint32_t st = row_stats(xr);
    if (lane == 0) asm volatile("st.relaxed.gpu.global.u32 [%0], %1;" ::"l"(g_stats + blockIdx.x * 16 + warp), "r"(st) : "memory");
  }
  if (is_conv && warp == 15 && elect_one()) {
    mbar_init(sbase + A_BAR, 1);
    mbar_init(sbase + A_BAR + 8, 16);
    fence_proxy_async();
    mbar_expect_tx(sbase + A_BAR, 32768);
    tma_load_3d(sbase + A_XST, &tm_x, (int)(blockIdx.x >> 1) * 8, 0, 0, sbase + A_BAR);
  }
  if (!is_conv) {
    const int hb = blockIdx.x - A_CONV_CTAS;
    if (hb == 19 && tid == 0) g_epoch[0] = g_epoch[0] + 1u;
    if (tid == 0) {
      for (int i = hb; i < 98; i += 20)
        asm volatile("cp.async.bulk.prefetch.L2.global [%0], %1;" ::"l"((const char*)P.wd + (size_t)i * 16384), "r"(16384) : "memory");
    }
    float* red = reinterpret_cast<float*>(smem);
    const int cc = lane & 7, rg = tid >> 3;
#pragma unroll 1
    for (int k = 0; k < 3; k++) {
      const int unit = hb + 20 * k;
      if (unit < 56) {
        const __nv_bfloat16* W = ((unit < 28) ? P.wg : P.wu) + (size_t)rg * F_ + (unit % 28) * 64 + cc * 8;
        uint4 v[7];
#pragma unroll
        for (int j = 0; j < 7; j++) v[j] = __ldg(reinterpret_cast<const uint4*>(W + (size_t)64 * j * F_));
        if (unit + 20 < 56) {
          const int u2 = unit + 20;
          const __nv_bfloat16* W2 = ((u2 < 28) ? P.wg : P.wu) + (size_t)rg * F_ + (u2 % 28) * 64;
          if (cc < 7) asm volatile("prefetch.global.L2 [%0];" ::"l"(W2 + (size_t)64 * cc * F_));
        }
        float s[8];
#pragma unroll
        for (int i = 0; i < 8; i++) s[i] = 0.f;
#pragma unroll
        for (int j = 0; j < 7; j++) {
          s[0] += bf_lo(v[j].x); s[1] += bf_hi(v[j].x); s[2] += bf_lo(v[j].y); s[3] += bf_hi(v[j].y);
          s[4] += bf_lo(v[j].z); s[5] += bf_hi(v[j].z); s[6] += bf_lo(v[j].w); s[7] += bf_hi(v[j].w);
        }
#pragma unroll
        for (int i = 0; i < 8; i++) {
          s[i] += __shfl_xor_sync(0xffffffffu, s[i], 8);
          s[i] += __shfl_xor_sync(0xffffffffu, s[i], 16);
        }
        if (lane < 8) {
          float4* rp = reinterpret_cast<float4*>(red + (k * 16 + warp) * 64 + lane * 8);
          rp[0] = make_float4(s[0], s[1], s[2], s[3]);
          rp[1] = make_float4(s[4], s[5], s[6], s[7]);
        }
      }
    }
    __syncthreads();
    if (tid < 192 && hb + 20 * (tid >> 6) < 56) {
      float a = 0.f;
#pragma unroll
      for (int w = 0; w < 16; w++) a += red[((tid >> 6) * 16 + w) * 64 + (tid & 63)];
      g_csum[(hb + 20 * (tid >> 6)) * 64 + (tid & 63)] = a;
    }
    return;
  }
  const int w = warp & 3, g = lane >> 2, t4 = lane & 3;
  const uint32_t wgreg = sbase + wg * A_WGREG;
  const uint32_t kc = wgreg;
  uint4 ki[2];
  uint32_t ki9[2];
  const uint32_t krev = wgreg + WG_KREV;
  {
    const float dt = bf_round(__expf(ldt));
    cplx w0, w1;
    {
      cplx b0, c0, b1, c1;
      b0.r = dt * bf_lo(pm[2]); b0.i = dt * bf_lo(pm[3]); c0.r = bf_lo(pm[4]); c0.i = bf_lo(pm[5]);
      b1.r = dt * bf_hi(pm[2]); b1.i = dt * bf_hi(pm[3]); c1.r = bf_hi(pm[4]); c1.i = bf_hi(pm[5]);
      w0 = cmul(c0, b0);
      w1 = cmul(c1, b1);
    }
    const Anchors A0 = kgen_anchors(dt * bf_lo(pm[0]), dt * bf_lo(pm[1])), A1 = kgen_anchors(dt * bf_hi(pm[0]), dt * bf_hi(pm[1]));
    uint32_t eb = __float_as_uint(fmaxf(fmaxf(fabsf(w0.r), fabsf(w0.i)), fmaxf(fabsf(w1.r), fabsf(w1.i)))) >> 23;
    eb = __reduce_max_sync(0xffffffffu, eb);
    if (lane == 0) asm volatile("st.shared.u32 [%0], %1;" ::"r"(sbase + A_BAR + 16 + warp * 4), "r"(eb) : "memory");
    bar_sync(1, 512);
    {
      const uint4 e4 = lds128(sbase + A_BAR + 16 + wg * 16);
      eb = min(max(max(max(e4.x, e4.y), max(e4.z, e4.w)), 1u), 253u);
    }
    const float sc = __uint_as_float((254u - eb) << 23), isc = __uint_as_float(eb << 23);
    float dk[24];
    uint32_t st[8];
#pragma unroll 1
    for (int r = 0; r < 2; r++) {
      cplx ww;
      ww.r = (r ? w1.r : w0.r) * sc;
      ww.i = (r ? w1.i : w0.i) * sc;
      kgen_tables(A0, A1, r > 0, ww, wgreg, tid128, 3 + wg);
      if (r == 1) {
        asm volatile("ld.relaxed.gpu.global.v4.u32 {%0,%1,%2,%3}, [%4];" : "=r"(st[0]), "=r"(st[1]), "=r"(st[2]), "=r"(st[3]) : "l"(g_stats + (tid & 255) * 8) : "memory");
        asm volatile("ld.relaxed.gpu.global.v4.u32 {%0,%1,%2,%3}, [%4];" : "=r"(st[4]), "=r"(st[5]), "=r"(st[6]), "=r"(st[7]) : "l"(g_stats + (tid & 255) * 8 + 4) : "memory");
#pragma unroll
        for (int j = 0; j < 2; j++) {
          ki[j] = __ldg(reinterpret_cast<const uint4*>(c_kidx) + tid128 + 128 * j);
          ki9[j] = c_kidx[(tid128 + 128 * j) * 8 + 8];
        }
      }
      WG_FENCE();
#pragma unroll
      for (int k = 0; k < 8; k++)
        wgmma_ss_f16_n48<1, 1>(dk, mkdesc(wgreg + k * 2048, 8192, 1024, 1), mkdesc(wgreg + 16384 + k * 2048, 8192, 1024, 1), r + k > 0);
      WG_COMMIT();
    }
    WG_WAIT(0);
    bar_sync(3 + wg, 128);
    {
      const uint32_t pa = wgreg + (w >> 1) * KC_HALF + (uint32_t)((2 * t4 * KC_PITCH + 16 * (w & 1) + g) * 4);
#pragma unroll
      for (int j = 0; j < 3; j++)
#pragma unroll
        for (int k = 0; k < 4; k++)
          asm volatile("st.shared.f32 [%0], %1;" ::"r"(pa + ((8 * j + (k & 1)) * KC_PITCH + 8 * (k >> 1)) * 4), "f"(((w < 2) ? dk[4 * j + k] : dk[12 + 4 * j + k]) * isc) : "memory");
    }
    {
      const int i = tid & 255, cp = tid >> 8;
      int it = 0;
      while (min(min(min(st[0], st[1]), min(st[2], st[3])), min(min(st[4], st[5]), min(st[6], st[7]))) == 0u && ++it < (1 << 20)) {
        asm volatile("ld.relaxed.gpu.global.v4.u32 {%0,%1,%2,%3}, [%4];" : "=r"(st[0]), "=r"(st[1]), "=r"(st[2]), "=r"(st[3]) : "l"(g_stats + i * 8) : "memory");
        asm volatile("ld.relaxed.gpu.global.v4.u32 {%0,%1,%2,%3}, [%4];" : "=r"(st[4]), "=r"(st[5]), "=r"(st[6]), "=r"(st[7]) : "l"(g_stats + i * 8 + 4) : "memory");
      }
      mbar_wait(sbase + A_BAR, 0);
      uint32_t xw[8], uw[8];
      const uint32_t xa = sbase + A_XST + i * 16 + (blockIdx.x & 1) * 8 + cp * 4;
#pragma unroll
      for (int t = 0; t < 8; t++) xw[t] = lds32(xa + t * 4096);
#pragma unroll
      for (int t = 0; t < 8; t++) {
        float rr;
        asm("rcp.approx.f32 %0, %1;" : "=f"(rr) : "f"(bf_hi(st[t])));
        const uint32_t dd = bf2_add(xw[t], __byte_perm(st[t], 0u, 0x1010u) ^ 0x80008000u);
        uw[t] = pack_bf16(bf_lo(dd) * rr, bf_hi(dd) * rr);
      }
      const uint32_t ub = sbase + A_UPL + cp * 4 * UPL_PLANE + UPL_PAD + (i & 1) * UPL_PLANE + (i >> 1) * 16, xb = sbase + A_XS + cp * 8192 + i * 16;
#pragma unroll
      for (int cc = 0; cc < 2; cc++) {
        const uint32_t sel = cc ? 0x7632u : 0x5410u;
        sts128(ub + cc * 2 * UPL_PLANE, __byte_perm(uw[0], uw[1], sel), __byte_perm(uw[2], uw[3], sel), __byte_perm(uw[4], uw[5], sel), __byte_perm(uw[6], uw[7], sel));
        sts128(xb + cc * 4096, __byte_perm(xw[0], xw[1], sel), __byte_perm(xw[2], xw[3], sel), __byte_perm(xw[4], xw[5], sel), __byte_perm(xw[6], xw[7], sel));
      }
      if ((tid & 63) < 60) sts128(sbase + A_UPL + (tid >> 6) * UPL_PLANE + (tid & 63) * 16, 0u, 0u, 0u, 0u);
      fence_proxy_async();
      __syncwarp();
      if (lane == 0) mbar_arrive(sbase + A_BAR + 8);
    }
    bar_sync(3 + wg, 128);
#pragma unroll
    for (int j = 0; j < 2; j++) {
      float v[9];
      const uint32_t io[9] = {ki[j].x & 0xFFFFu, ki[j].x >> 16, ki[j].y & 0xFFFFu, ki[j].y >> 16, ki[j].z & 0xFFFFu, ki[j].z >> 16, ki[j].w & 0xFFFFu, ki[j].w >> 16, ki9[j]};
#pragma unroll
      for (int n = 0; n < 9; n++) v[n] = __uint_as_float(lds32(kc + io[n])) + __uint_as_float(lds32(kc + KC_HALF + io[n]));
      const uint32_t o = (uint32_t)((tid128 + 128 * j) * 16);
      sts128(krev + o, pack_bf16(v[0], v[1]), pack_bf16(v[2], v[3]), pack_bf16(v[4], v[5]), pack_bf16(v[6], v[7]));
      sts128(krev + KREV_COPY + o, pack_bf16(v[1], v[2]), pack_bf16(v[3], v[4]), pack_bf16(v[5], v[6]), pack_bf16(v[7], v[8]));
    }
    if (tid128 < 8) {
      const uint32_t k0 = (tid128 == 0) ? pack_bf16(__uint_as_float(lds32(kc)) + __uint_as_float(lds32(kc + KC_HALF)), 0.f) : 0u;
      sts128(krev + (tid128 >> 2) * KREV_COPY + 4096 + (tid128 & 3) * 16, k0, 0u, 0u, 0u);
    }
  }
  bar_sync(3 + wg, 128);
  mbar_wait(sbase + A_BAR + 8, 0);
  if (wg >= 2) bar_sync(2, 512);
  float acc[64];
  const uint32_t upl = sbase + A_UPL + wg * 2 * UPL_PLANE + UPL_PAD;
  {
    const uint32_t kaddr = (g & 1) ? (krev + KREV_COPY + 2 * (2047 - 16 * w - g + 2 * t4)) : (krev + 2 * (2048 - 16 * w - g + 2 * t4));
    const uint64_t db = mkdesc(upl, UPL_PLANE, 128, 0);
    float c3[16], c2[32];
    const float fz = __uint_as_float(lds32(upl - 16));
    {
      uint32_t a[2][4][4];
      conv_frags4<24>(a[0], kaddr);
#pragma unroll
      for (int bt = 0; bt < 4; bt++) {
        WG_FENCE();
#pragma unroll
        for (int s = 0; s < 4; s++) {
          if (bt < 2) wgmma_rs_n32<0>(c3, a[bt & 1][s][0], a[bt & 1][s][1], a[bt & 1][s][2], a[bt & 1][s][3], db - (uint64_t)(16 * bt + 4 * s), bt + s > 0);
          else wgmma_rs_n64<0>(c2, a[bt & 1][s][0], a[bt & 1][s][1], a[bt & 1][s][2], a[bt & 1][s][3], db - (uint64_t)(16 * (bt - 2) + 4 * s), bt - 2 + s > 0);
        }
        WG_COMMIT();
        if (bt > 0) WG_WAIT(1);
        if (bt == 0) conv_frags4<28>(a[1], kaddr);
        if (bt == 1) conv_frags4<16>(a[0], kaddr);
        if (bt == 2) conv_frags4<20>(a[1], kaddr);
      }
      WG_WAIT(0);
    }
#pragma unroll
    for (int i = 0; i < 16; i++) { acc[48 + i] = c2[16 + i] + c3[i]; acc[32 + i] = c2[i] + fz; }
#pragma unroll
    for (int i = 0; i < 32; i++) acc[i] = fz;
    {
      uint32_t a[2][4][4];
      conv_frags4<0>(a[0], kaddr);
#pragma unroll
      for (int bt = 0; bt < 4; bt++) {
        WG_FENCE();
#pragma unroll
        for (int s = 0; s < 4; s++)
          wgmma_rs_n128<0>(acc, a[bt & 1][s][0], a[bt & 1][s][1], a[bt & 1][s][2], a[bt & 1][s][3], db - (uint64_t)(16 * bt + 4 * s), 1);
        WG_COMMIT();
        if (bt > 0) WG_WAIT(1);
        if (bt == 0) conv_frags4<4>(a[1], kaddr);
        if (bt == 1) conv_frags4<8>(a[0], kaddr);
        if (bt == 2) conv_frags4<12>(a[1], kaddr);
      }
      WG_WAIT(0);
    }
  }
  if (wg < 2) bar_arrive(2, 512);
  {
    bar_sync(3 + wg, 128);
    const uint32_t wb = wgreg + w * EPI_WARP + (uint32_t)((g * EPI_PITCH + 4 + 2 * t4) * 4);
#pragma unroll
    for (int j = 0; j < 16; j++) {
      asm volatile("st.shared.v2.f32 [%0], {%1,%2};" ::"r"(wb + j * 32), "f"(acc[4 * j]), "f"(acc[4 * j + 1]) : "memory");
      asm volatile("st.shared.v2.f32 [%0], {%1,%2};" ::"r"(wb + 8 * EPI_PITCH * 4 + j * 32), "f"(acc[4 * j + 2]), "f"(acc[4 * j + 3]) : "memory");
    }
    if (lane < 16) sts128(wgreg + w * EPI_WARP + lane * EPI_PITCH * 4, 0u, 0u, 0u, 0u);
  }
  bar_sync(3 + wg, 128);
  {
    const uint32_t rb = wgreg + (uint32_t)((4 + tid128) * 4);
    __nv_bfloat16* hrow = g_hT + (size_t)d * L_ + tid128 * 16;
    const uint32_t dsk2 = pack_bf16(dskip, dskip);
#pragma unroll 1
    for (int hf = 0; hf < 2; hf++) {
      float y[8];
#pragma unroll
      for (int i = 0; i < 8; i++) {
        const uint32_t o = rb + (uint32_t)((hf * 8 + i) * EPI_PITCH * 4);
        y[i] = (__uint_as_float(lds32(o)) + __uint_as_float(lds32(o + EPI_WARP - 4))) +
               (__uint_as_float(lds32(o + 2 * EPI_WARP - 8)) + __uint_as_float(lds32(o + 3 * EPI_WARP - 12)));
      }
      const uint4 uu = lds128(upl + hf * UPL_PLANE + tid128 * 16);
      const uint4 xx = lds128(sbase + A_XS + wg * 4096 + tid128 * 32 + hf * 16);
      const uint32_t uw[4] = {uu.x, uu.y, uu.z, uu.w}, xw[4] = {xx.x, xx.y, xx.z, xx.w};
      uint32_t o[4];
#pragma unroll
      for (int i = 0; i < 4; i++) {
        o[i] = bf2_add(xw[i], bf2_add(pack_bf16(y[2 * i], y[2 * i + 1]), bf2_mul(uw[i], dsk2)));
      }
      *reinterpret_cast<uint4*>(hrow + hf * 8) = make_uint4(o[0], o[1], o[2], o[3]);
    }
  }
}

constexpr int B_THREADS = 384;
constexpr int B_HT = 0;
constexpr int B_RING = 114688;
constexpr int NSLOT = 7;
constexpr int B_CS = B_RING + NSLOT * 16384;
constexpr int B_BAR = B_CS + 448 * 4 + 16;
constexpr int B_SMEM = B_BAR + 24 * 8 + 128;
constexpr int BAR_FULL = 0, BAR_EMPTY = 7, BAR_H = 14;

__device__ __forceinline__ float glu_act(float ag, float au, float cg, float cu, float2 s) {
  const float x = fmaf(s.x, cg, ag) * s.y;
  const float u = fmaf(s.x, cu, au);
  float th;
  asm("tanh.approx.f32 %0, %1;" : "=f"(th) : "f"(x));
  return fmaf(th, u, u);
}
__device__ __forceinline__ void glu_block(const float* ag, const float* au, uint32_t csa, float2 s0, float2 s1, uint32_t& o0, uint32_t& o1) {
  const uint2 cgw = lds64(csa), cuw = lds64(csa + 224 * 4);
  const float cg0 = __uint_as_float(cgw.x), cg1 = __uint_as_float(cgw.y), cu0 = __uint_as_float(cuw.x), cu1 = __uint_as_float(cuw.y);
  o0 = pack_bf16(glu_act(ag[0], au[0], cg0, cu0, s0), glu_act(ag[1], au[1], cg1, cu1, s0));
  o1 = pack_bf16(glu_act(ag[2], au[2], cg0, cu0, s1), glu_act(ag[3], au[3], cg1, cu1, s1));
}
__device__ __forceinline__ float2 ln_consts(float sm, float sq) {
  const float mean = sm * (1.f / D_);
  const float var = bf_round(fmaxf(fmaf(-mean, mean, sq * (1.f / D_)), 0.f));
  float den;
  asm("sqrt.approx.f32 %0, %1;" : "=f"(den) : "f"(bf_round(var + 1e-5f)));
  return make_float2(-bf_round(mean), __fdividef(0.5f, bf_round(den)));
}
__device__ __forceinline__ uint4 ldg_frag(const uint4* p) {
  unsigned long long a, c;
  asm volatile("ld.relaxed.gpu.global.v2.b64 {%0,%1}, [%2];" : "=l"(a), "=l"(c) : "l"(p) : "memory");
  return make_uint4((uint32_t)a, (uint32_t)(a >> 32), (uint32_t)c, (uint32_t)(c >> 32));
}
__device__ __forceinline__ void stg_frag(uint4* p, uint4& v, uint32_t ep) {
  v.x = (v.x & ~1u) | ep;
  v.z = (v.z & ~1u) | ep;
  const unsigned long long a = (unsigned long long)v.x | ((unsigned long long)v.y << 32), c = (unsigned long long)v.z | ((unsigned long long)v.w << 32);
  asm volatile("st.relaxed.gpu.global.v2.b64 [%0], {%1,%2};" ::"l"(p), "l"(a), "l"(c) : "memory");
}
template <int NK>
__device__ __forceinline__ void load_frags(uint4 (&f)[NK], const uint4* src) {
#pragma unroll
  for (int k = 0; k < NK; k++) f[k] = ldg_frag(src + k * 32);
}
template <int NK>
__device__ __forceinline__ void check_frags(uint4 (&f)[NK], const uint4* src, uint32_t ep) {
#pragma unroll 1
  for (int it = 0; it < (1 << 18); it++) {
    uint32_t bad = 0;
#pragma unroll
    for (int k = 0; k < NK; k++) bad |= (f[k].x ^ ep) | (f[k].z ^ ep);
    if (!__any_sync(0xffffffffu, bad & 1u)) break;
    if (it > 0) __nanosleep(100);
    load_frags<NK>(f, src);
  }
}

__device__ __forceinline__ void ln2_stats(uint32_t sbase, int half, int slice, int rt, int lane) {
  const uint32_t bars = sbase + B_BAR;
  const uint32_t sta = sbase + B_HT + (slice >> 2) * 7 * 8192 + half * 14 * 2048 + ((lane & 7) + 8 * (lane >> 4)) * 128 +
                       (((2 * (slice & 3) + ((lane >> 3) & 1)) ^ (lane & 7)) << 4);
  float sm0 = 0.f, sq0 = 0.f, sm1 = 0.f, sq1 = 0.f;
#pragma unroll 1
  for (int k2 = 0; k2 < 7; k2++) {
    mbar_wait(bars + (BAR_H + ((half * 14 + 2 * k2 + 1) >> 2)) * 8, 0);
    uint32_t a[8];
    ldsm_x4_t(a[0], a[1], a[2], a[3], sta + k2 * 4096);
    ldsm_x4_t(a[4], a[5], a[6], a[7], sta + k2 * 4096 + 2048);
#pragma unroll
    for (int i = 0; i < 8; i += 2) {
      const float x0 = bf_lo(a[i]), x1 = bf_hi(a[i]), y0 = bf_lo(a[i + 1]), y1 = bf_hi(a[i + 1]);
      sm0 += x0 + x1; sq0 = fmaf(x0, x0, fmaf(x1, x1, sq0));
      sm1 += y0 + y1; sq1 = fmaf(y0, y0, fmaf(y1, y1, sq1));
    }
  }
#pragma unroll
  for (int o = 1; o < 4; o <<= 1) {
    sm0 += __shfl_xor_sync(0xffffffffu, sm0, o); sq0 += __shfl_xor_sync(0xffffffffu, sq0, o);
    sm1 += __shfl_xor_sync(0xffffffffu, sm1, o); sq1 += __shfl_xor_sync(0xffffffffu, sq1, o);
  }
  const uint32_t xa = sbase + B_BAR + 24 * 8 + (lane >> 2) * 16;
  if (half == 0) {
    if ((lane & 3) == 0) sts128(xa, __float_as_uint(sm0), __float_as_uint(sq0), __float_as_uint(sm1), __float_as_uint(sq1));
    bar_arrive(7, 64);
  } else {
    bar_sync(7, 64);
    const uint4 o = lds128(xa);
    const uint32_t ep = lds32(sbase + B_CS + 1792) & 1u;
    const bool hi = lane & 1;
    const float2 sc = ln_consts(hi ? sm1 + __uint_as_float(o.z) : sm0 + __uint_as_float(o.x), hi ? sq1 + __uint_as_float(o.w) : sq0 + __uint_as_float(o.y));
    const unsigned long long v = (unsigned long long)((__float_as_uint(sc.y) & ~1u) | ep) | ((unsigned long long)__float_as_uint(sc.x) << 32);
    if ((lane & 2) == 0)
      asm volatile("st.relaxed.gpu.global.b64 [%0], %1;" ::"l"(g_st2 + rt * 128 + slice * 16 + (lane >> 2) + 8 * (lane & 1)), "l"(v) : "memory");
  }
}

template <int U0, int NK>
__device__ __forceinline__ void g2_group(float (&acc)[56], const uint4 (&fr)[NK], uint32_t sbase, uint32_t ebase, bool elect) {
#pragma unroll
  for (int k = 0; k < NK; k += 2) {
    const int u = U0 + k / 2;
    const int fill = 28 + u / 2, slot = fill % NSLOT;
    if ((u & 1) == 0) mbar_wait(sbase + B_BAR + (BAR_FULL + slot) * 8, (fill / NSLOT) & 1);
    const uint32_t bb = sbase + B_RING + slot * 16384 + (u & 1) * 8192;
    WG_FENCE();
    wgmma_rs_n112<1>(acc, fr[k].x, fr[k].y, fr[k].z, fr[k].w, mkdesc(bb, 4096, 1024, 1), u == 0 ? 0 : 1);
    wgmma_rs_n112<1>(acc, fr[k + 1].x, fr[k + 1].y, fr[k + 1].z, fr[k + 1].w, mkdesc(bb + 2048, 4096, 1024, 1), 1);
    WG_COMMIT();
    WG_WAIT(1);
    if (u >= 2 && (u & 1) == 0 && 28 + (u - 1) / 2 + NSLOT < 42) {
      const int pf = 28 + (u - 1) / 2;
      release_slot(ebase, pf % NSLOT, elect);
    }
  }
}

__global__ void __cluster_dims__(2, 1, 1) __launch_bounds__(B_THREADS, 1)
glu_kernel(const __grid_constant__ CUtensorMap tm_h, const __grid_constant__ CUtensorMap tm_wg, const __grid_constant__ CUtensorMap tm_wu,
           const __grid_constant__ CUtensorMap tm_wg32, const __grid_constant__ CUtensorMap tm_wu32, const __grid_constant__ CUtensorMap tm_wd,
           __nv_bfloat16* __restrict__ out) {
  extern __shared__ __align__(1024) unsigned char smem[];
  const int tid = threadIdx.x, warp = __shfl_sync(0xffffffffu, tid >> 5, 0), lane = tid & 31;
  const uint32_t sbase = smem_u32(smem);
  const int crank = blockIdx.x & 1, slice = (blockIdx.x >> 1) & 7, rt = (blockIdx.x >> 4) * 2 + crank;
  const int q = slice & 3, rank = slice >> 2;
  const int f0 = slice * 224;
  const uint32_t bars = sbase + B_BAR;
  if (elect_one()) {
#pragma unroll
    for (int i = 0; i < 2; i++) {
      const int bi = warp + 12 * i;
      if (bi < 21) mbar_init(bars + bi * 8, (bi >= BAR_EMPTY && bi < BAR_H) ? 4 : 1);
    }
    if (warp == 8) asm volatile("prefetch.tensormap [%0];" ::"l"((uint64_t)(crank ? &tm_wu : &tm_wg)) : "memory");
    if (warp == 9) {
      asm volatile("prefetch.tensormap [%0];" ::"l"((uint64_t)(crank ? &tm_wu32 : &tm_wg32)) : "memory");
      asm volatile("prefetch.tensormap [%0];" ::"l"((uint64_t)&tm_wd) : "memory");
    }
    if (warp == 10) asm volatile("prefetch.tensormap [%0];" ::"l"((uint64_t)&tm_h) : "memory");
    asm volatile("fence.mbarrier_init.release.cluster;" ::: "memory");
  }
  __syncwarp();
  asm volatile("barrier.cluster.arrive.relaxed.aligned;\nbarrier.cluster.wait.acquire.aligned;" ::: "memory");
  if (warp >= 8) {
    asm volatile("setmaxnreg.dec.sync.aligned.u32 40;");
    if (warp < 10) {
      if (warp == 8) {
        int slot = 0, wrap = 0;
#pragma unroll 1
        for (int fill = 0; fill < 42; fill++) {
          const uint32_t fb = bars + (BAR_FULL + slot) * 8;
          const uint32_t dst = sbase + B_RING + slot * 16384;
          if (wrap > 0) mbar_wait_cluster(bars + (BAR_EMPTY + slot) * 8, (wrap - 1) & 1);
          if (elect_one()) {
            if (fill < 14) {
              mbar_expect_tx(fb, 16384);
              tma_load_3d_mc(dst + crank * 8192, crank ? &tm_wu : &tm_wg, f0, fill * 32, 0, fb);
            } else if (fill < 28) {
              mbar_expect_tx(fb, 12288);
              tma_load_3d_mc(dst + crank * 6144, crank ? &tm_wu32 : &tm_wg32, f0 + 128, (fill - 14) * 32, 0, fb);
            } else {
              mbar_expect_tx(fb, 16384);
              const int u = (fill - 28) * 2 + crank;
              int fr;
              if (u < 7) fr = f0 + u * 32;
              else if (u < 19) fr = (rank * 4 + ((q + 1 + (u - 7) / 4) & 3)) * 224 + ((u - 7) & 3) * 32;
              else fr = (rank * 4 + ((q + 1 + (u - 19) / 3) & 3)) * 224 + 128 + ((u - 19) % 3) * 32;
              tma_load_2d_mc(dst + crank * 8192, &tm_wd, q * 112, fr, fb);
              tma_load_2d_mc(dst + crank * 8192 + 4096, &tm_wd, q * 112 + 64, fr, fb);
            }
          }
          __syncwarp();
          if (++slot == NSLOT) { slot = 0; wrap++; }
        }
      } else {
        ln2_stats(sbase, 0, slice, rt, lane);
      }
    } else {
      asm volatile("griddepcontrol.wait;" ::: "memory");
      if (warp == 10) {
        if (elect_one()) {
#pragma unroll 1
          for (int c = 0; c < 7; c++) {
            const uint32_t hb = bars + (BAR_H + c) * 8;
            mbar_expect_tx(hb, c == 6 ? 16384 + 1792 + 16 : 16384);
            tma_load_2d(sbase + B_HT + c * 8192, &tm_h, rt * 128, c * 64, hb);
            tma_load_2d(sbase + B_HT + (7 + c) * 8192, &tm_h, rt * 128 + 64, c * 64, hb);
          }
          asm volatile("cp.async.bulk.shared::cluster.global.mbarrier::complete_tx::bytes [%0], [%1], 896, [%2];"
                       ::"r"(sbase + B_CS), "l"(g_csum + f0), "r"(bars + (BAR_H + 6) * 8) : "memory");
          asm volatile("cp.async.bulk.shared::cluster.global.mbarrier::complete_tx::bytes [%0], [%1], 896, [%2];"
                       ::"r"(sbase + B_CS + 896), "l"(g_csum + F_ + f0), "r"(bars + (BAR_H + 6) * 8) : "memory");
          asm volatile("cp.async.bulk.shared::cluster.global.mbarrier::complete_tx::bytes [%0], [%1], 16, [%2];"
                       ::"r"(sbase + B_CS + 1792), "l"(g_epoch), "r"(bars + (BAR_H + 6) * 8) : "memory");
        }
        __syncwarp();
      } else {
        if (lane < 16) g_stats[blockIdx.x * 16 + lane] = 0u;
        ln2_stats(sbase, 1, slice, rt, lane);
      }
    }
  } else {
    asm volatile("setmaxnreg.inc.sync.aligned.u32 232;");
    const int w = warp >> 2, wq = warp & 3, g = lane >> 2, t4 = lane & 3;
    const bool elect = (tid & 127) < 2;
    uint32_t ebase;
    asm volatile("mapa.shared::cluster.u32 %0, %1, %2;" : "=r"(ebase) : "r"(bars + BAR_EMPTY * 8), "r"(lane & 1));
    const uint32_t ht = sbase + B_HT + w * 7 * 8192;
    uint4 H1[8], H2[6];
    uint4* hout = g_H + ((size_t)((rt * 8 + slice) * 8 + warp) * 14) * 32 + lane;
    const uint32_t csa = sbase + B_CS + t4 * 8;
    float2 s0, s1;
    uint32_t ep;
    {
      float acc[128];
      int slot = 0;
#pragma unroll 1
      for (int u = 0; u < 14; u++) {
        if ((u & 1) == 0) mbar_wait(bars + (BAR_H + (u >> 1)) * 8, 0);
        mbar_wait(bars + (BAR_FULL + slot) * 8, u >= NSLOT);
        const uint32_t aa = ht + u * 4096, bb = sbase + B_RING + slot * 16384;
        WG_FENCE();
        wgmma_ss_n256<1, 1>(acc, mkdesc(aa, 8192, 1024, 1), mkdesc(bb, 4096, 1024, 1), u > 0);
        wgmma_ss_n256<1, 1>(acc, mkdesc(aa + 2048, 8192, 1024, 1), mkdesc(bb + 2048, 4096, 1024, 1), 1);
        WG_COMMIT();
        WG_WAIT(1);
        release_slot(ebase, slot == 0 ? NSLOT - 1 : slot - 1, u > 0 && elect);
        if (++slot == NSLOT) slot = 0;
      }
      ep = lds32(sbase + B_CS + 1792) & 1u;
      {
        const uint2* sp = g_st2 + rt * 128 + w * 64 + wq * 16 + g;
#pragma unroll 1
        for (int it = 0; it < (1 << 18); it++) {
          unsigned long long a, c;
          asm volatile("ld.relaxed.gpu.global.b64 %0, [%1];" : "=l"(a) : "l"(sp) : "memory");
          asm volatile("ld.relaxed.gpu.global.b64 %0, [%1];" : "=l"(c) : "l"(sp + 8) : "memory");
          s0 = make_float2(__uint_as_float((uint32_t)(a >> 32)), __uint_as_float((uint32_t)a));
          s1 = make_float2(__uint_as_float((uint32_t)(c >> 32)), __uint_as_float((uint32_t)c));
          if (!__any_sync(0xffffffffu, (((uint32_t)a ^ ep) | ((uint32_t)c ^ ep)) & 1u)) break;
        }
      }
      WG_WAIT(0);
      release_slot(ebase, 13 % NSLOT, elect);
#pragma unroll
      for (int kb = 0; kb < 8; kb++) {
        glu_block(&acc[8 * kb], &acc[64 + 8 * kb], csa + 64 * kb, s0, s1, H1[kb].x, H1[kb].y);
        glu_block(&acc[8 * kb + 4], &acc[64 + 8 * kb + 4], csa + 64 * kb + 32, s0, s1, H1[kb].z, H1[kb].w);
        stg_frag(hout + kb * 32, H1[kb], ep);
      }
    }
    const uint4* hsrc[3];
#pragma unroll
    for (int j = 0; j < 3; j++) hsrc[j] = g_H + ((size_t)((rt * 8 + rank * 4 + ((q + 1 + j) & 3)) * 8 + warp) * 14) * 32 + lane;
    uint4 Fa[8], Fb[8];
    {
      float acc[96];
#pragma unroll
      for (int hf = 0; hf < 2; hf++) {
#pragma unroll 1
        for (int slot = 0; slot < NSLOT; slot++) {
          const int u = hf * NSLOT + slot;
          mbar_wait(bars + (BAR_FULL + slot) * 8, hf);
          const uint32_t aa = ht + u * 4096, bb = sbase + B_RING + slot * 16384;
          WG_FENCE();
          wgmma_ss_n192<1, 1>(acc, mkdesc(aa, 8192, 1024, 1), mkdesc(bb, 2048, 512, 2), u > 0);
          wgmma_ss_n192<1, 1>(acc, mkdesc(aa + 2048, 8192, 1024, 1), mkdesc(bb + 1024, 2048, 512, 2), 1);
          WG_COMMIT();
          WG_WAIT(1);
          release_slot(ebase, slot == 0 ? NSLOT - 1 : slot - 1, u > 0 && elect);
        }
        if (hf == 0) {
          load_frags<8>(Fa, hsrc[0]);
          load_frags<8>(Fb, hsrc[1]);
        }
      }
      WG_WAIT(0);
      release_slot(ebase, 27 % NSLOT, elect);
#pragma unroll
      for (int kb = 0; kb < 6; kb++) {
        glu_block(&acc[8 * kb], &acc[48 + 8 * kb], csa + 512 + 64 * kb, s0, s1, H2[kb].x, H2[kb].y);
        glu_block(&acc[8 * kb + 4], &acc[48 + 8 * kb + 4], csa + 512 + 64 * kb + 32, s0, s1, H2[kb].z, H2[kb].w);
        stg_frag(hout + (8 + kb) * 32, H2[kb], ep);
      }
    }
    float acc[56];
    {
      uint4 Fc[8];
      uint4 Ga[6], Gb[6], Gc[6];
      g2_group<0, 8>(acc, H1, sbase, ebase, elect);
      check_frags<8>(Fa, hsrc[0], ep);
      check_frags<8>(Fb, hsrc[1], ep);
      load_frags<8>(Fc, hsrc[2]);
      g2_group<4, 6>(acc, H2, sbase, ebase, elect);
      g2_group<7, 8>(acc, Fa, sbase, ebase, elect);
      check_frags<8>(Fc, hsrc[2], ep);
      load_frags<6>(Ga, hsrc[0] + 8 * 32);
      load_frags<6>(Gb, hsrc[1] + 8 * 32);
      g2_group<11, 8>(acc, Fb, sbase, ebase, elect);
      check_frags<6>(Ga, hsrc[0] + 8 * 32, ep);
      check_frags<6>(Gb, hsrc[1] + 8 * 32, ep);
      load_frags<6>(Gc, hsrc[2] + 8 * 32);
      g2_group<15, 8>(acc, Fc, sbase, ebase, elect);
      g2_group<19, 6>(acc, Ga, sbase, ebase, elect);
      g2_group<22, 6>(acc, Gb, sbase, ebase, elect);
      check_frags<6>(Gc, hsrc[2] + 8 * 32, ep);
      g2_group<25, 6>(acc, Gc, sbase, ebase, elect);
      WG_WAIT(0);
    }
    {
      uint4* pout = g_P + ((size_t)((rt * 8 + slice) * 8 + warp) * 7) * 32 + lane;
      const uint4* pin = g_P + ((size_t)((rt * 8 + (slice ^ 4)) * 8 + warp) * 7) * 32 + lane;
      float keep[28];
#pragma unroll
      for (int j = 0; j < 7; j++) {
        uint4 sv;
        sv.x = __float_as_uint(rank ? acc[4 * j] : acc[28 + 4 * j]);
        sv.y = __float_as_uint(rank ? acc[4 * j + 1] : acc[28 + 4 * j + 1]);
        sv.z = __float_as_uint(rank ? acc[4 * j + 2] : acc[28 + 4 * j + 2]);
        sv.w = __float_as_uint(rank ? acc[4 * j + 3] : acc[28 + 4 * j + 3]);
        stg_frag(pout + j * 32, sv, ep);
#pragma unroll
        for (int e = 0; e < 4; e++) keep[4 * j + e] = rank ? acc[28 + 4 * j + e] : acc[4 * j + e];
      }
      uint4 pv[7];
      uint32_t hr[7][2];
      const int dbase = 112 * q + 56 * rank;
      {
        const int mi = lane >> 3, r8 = lane & 7;
#pragma unroll
        for (int j = 0; j < 8; j += 2) {
          const int jj = j + (mi >> 1);
          const int dd = dbase + 8 * (jj < 7 ? jj : 6) + r8;
          const uint32_t ad = ht + dd * 128 + (((2 * wq + (mi & 1)) ^ r8) << 4);
          uint32_t r0, r1, r2, r3;
          ldsm_x4_t(r0, r1, r2, r3, ad);
          hr[j][0] = r0; hr[j][1] = r1;
          if (j + 1 < 7) { hr[j + 1][0] = r2; hr[j + 1][1] = r3; }
        }
      }
      {
        const uint4* pl = pin - lane + 6 * 32;
#pragma unroll 1
        for (int it = 0; it < (1 << 18); it++) {
          uint32_t v = ep;
          if (lane == 0) asm volatile("ld.relaxed.gpu.global.u32 %0, [%1];" : "=r"(v) : "l"(pl) : "memory");
          if (__all_sync(0xffffffffu, ((v ^ ep) & 1u) == 0u)) break;
          __nanosleep(64);
        }
      }
      load_frags<7>(pv, pin);
      check_frags<7>(pv, pin, ep);
      const int row = rt * 128 + w * 64 + wq * 16 + g;
      __nv_bfloat16* o0 = out + (size_t)row * D_ + dbase + 2 * t4;
#pragma unroll
      for (int j = 0; j < 7; j++) {
        const uint4 v = pv[j];
        const uint32_t a01 = pack_bf16((keep[4 * j] + __uint_as_float(v.x)) * s0.y, (keep[4 * j + 1] + __uint_as_float(v.y)) * s0.y);
        const uint32_t a23 = pack_bf16((keep[4 * j + 2] + __uint_as_float(v.z)) * s1.y, (keep[4 * j + 3] + __uint_as_float(v.w)) * s1.y);
        *reinterpret_cast<uint32_t*>(o0 + 8 * j) = bf2_add(hr[j][0], a01);
        *reinterpret_cast<uint32_t*>(o0 + 8 * D_ + 8 * j) = bf2_add(hr[j][1], a23);
      }
    }
  }
}

typedef CUresult (*EncodeFn)(CUtensorMap*, CUtensorMapDataType, cuuint32_t, void*, const cuuint64_t*, const cuuint64_t*, const cuuint32_t*,
                             const cuuint32_t*, CUtensorMapInterleave, CUtensorMapSwizzle, CUtensorMapL2promotion, CUtensorMapFloatOOBfill);

static void make_map(EncodeFn enc, CUtensorMap* tm, const void* ptr, uint64_t inner, uint64_t outer, uint32_t box_in, uint32_t box_out,
                     CUtensorMapSwizzle swz) {
  cuuint64_t gd[2] = {inner, outer};
  cuuint64_t gs[1] = {inner * 2};
  cuuint32_t bd[2] = {box_in, box_out};
  cuuint32_t es[2] = {1, 1};
  enc(tm, CU_TENSOR_MAP_DATA_TYPE_BFLOAT16, 2, const_cast<void*>(ptr), gd, gs, bd, es, CU_TENSOR_MAP_INTERLEAVE_NONE, swz,
      CU_TENSOR_MAP_L2_PROMOTION_L2_256B, CU_TENSOR_MAP_FLOAT_OOB_FILL_NONE);
}

static void make_map3(EncodeFn enc, CUtensorMap* tm, const void* ptr, uint32_t cols, uint32_t natoms, CUtensorMapSwizzle swz) {
  cuuint64_t gd[3] = {(cuuint64_t)(F_ - (natoms - 1) * cols), (cuuint64_t)D_, natoms};
  cuuint64_t gs[2] = {(cuuint64_t)F_ * 2, (cuuint64_t)cols * 2};
  cuuint32_t bd[3] = {cols, 32, natoms};
  cuuint32_t es[3] = {1, 1, 1};
  enc(tm, CU_TENSOR_MAP_DATA_TYPE_BFLOAT16, 3, const_cast<void*>(ptr), gd, gs, bd, es, CU_TENSOR_MAP_INTERLEAVE_NONE, swz,
      CU_TENSOR_MAP_L2_PROMOTION_L2_256B, CU_TENSOR_MAP_FLOAT_OOB_FILL_NONE);
}

extern "C" void kernel_launch(void* const* d_in, const int* in_sizes, int n_in, void* d_out, int out_size) {
  (void)in_sizes; (void)n_in; (void)out_size;
  static EncodeFn enc = nullptr;
  static void* hT_ptr = nullptr;
  if (!enc) {
    void* fn = nullptr;
    cudaDriverEntryPointQueryResult qr;
    cudaGetDriverEntryPoint("cuTensorMapEncodeTiled", &fn, cudaEnableDefault, &qr);
    enc = (EncodeFn)fn;
    cudaGetSymbolAddress(&hT_ptr, g_hT);
    cudaFuncSetAttribute(s4_conv_kernel, cudaFuncAttributeMaxDynamicSharedMemorySize, A_SMEM);
    cudaFuncSetAttribute(glu_kernel, cudaFuncAttributeMaxDynamicSharedMemorySize, B_SMEM);
  }
  const __nv_bfloat16* const* in = reinterpret_cast<const __nv_bfloat16* const*>(d_in);
  AParams P;
  P.x = in[0];
  for (int i = 0; i < 6; i++) P.p[i] = in[1 + i];
  P.log_dt = in[7];
  P.dskip = in[8];
  P.wg = in[10];
  P.wu = in[11];
  P.wd = in[12];
  CUtensorMap tm_h, tm_wg, tm_wu, tm_wg32, tm_wu32, tm_wd, tm_x;
  {
    cuuint64_t gd[3] = {(cuuint64_t)D_, 256, 8};
    cuuint64_t gs[2] = {(cuuint64_t)8 * D_ * 2, (cuuint64_t)D_ * 2};
    cuuint32_t bd[3] = {8, 256, 8};
    cuuint32_t es[3] = {1, 1, 1};
    enc(&tm_x, CU_TENSOR_MAP_DATA_TYPE_BFLOAT16, 3, const_cast<__nv_bfloat16*>(P.x), gd, gs, bd, es, CU_TENSOR_MAP_INTERLEAVE_NONE,
        CU_TENSOR_MAP_SWIZZLE_NONE, CU_TENSOR_MAP_L2_PROMOTION_NONE, CU_TENSOR_MAP_FLOAT_OOB_FILL_NONE);
  }
  make_map(enc, &tm_h, hT_ptr, L_, D_, 64, 64, CU_TENSOR_MAP_SWIZZLE_128B);
  make_map3(enc, &tm_wg, P.wg, 64, 2, CU_TENSOR_MAP_SWIZZLE_128B);
  make_map3(enc, &tm_wu, P.wu, 64, 2, CU_TENSOR_MAP_SWIZZLE_128B);
  make_map3(enc, &tm_wg32, P.wg, 32, 3, CU_TENSOR_MAP_SWIZZLE_64B);
  make_map3(enc, &tm_wu32, P.wu, 32, 3, CU_TENSOR_MAP_SWIZZLE_64B);
  make_map(enc, &tm_wd, P.wd, D_, F_, 64, 32, CU_TENSOR_MAP_SWIZZLE_128B);

  cudaStream_t stream = cudaStreamPerThread;
  s4_conv_kernel<<<A_GRID, A_THREADS, A_SMEM, stream>>>(P, tm_x);

  cudaLaunchConfig_t cfg = {};
  cfg.gridDim = dim3(128);
  cfg.blockDim = dim3(B_THREADS);
  cfg.dynamicSmemBytes = B_SMEM;
  cfg.stream = stream;
  cudaLaunchAttribute at[1];
  at[0].id = cudaLaunchAttributeProgrammaticStreamSerialization;
  at[0].val.programmaticStreamSerializationAllowed = 1;
  cfg.attrs = at;
  cfg.numAttrs = 1;
  cudaLaunchKernelEx(&cfg, glu_kernel, tm_h, tm_wg, tm_wu, tm_wg32, tm_wu32, tm_wd, (__nv_bfloat16*)d_out);
}
```
